```python
import torch

def _softmax(x, axis=-1):
    return torch.softmax(x, dim=axis)

def _gelu(x):
    return torch.nn.functional.gelu(x, approximate='tanh')

def _silu(x):
    return torch.nn.functional.silu(x)

def _sigmoid(x):
    return torch.sigmoid(x)

def _layernorm(x, axis=-1, eps=1e-05):
    m = x.mean(dim=axis, keepdim=True)
    v = x.var(dim=axis, keepdim=True, unbiased=False)
    return (x - m) / torch.sqrt(v + eps)

def _scatter_add(tgt, idx, src, axis=0):
    return tgt.clone().index_add_(axis, idx, src)

def _segment_sum(src, seg, n):
    out = torch.zeros((n,) + src.shape[1:], dtype=src.dtype)
    return out.index_add_(0, seg, src)

def _pad(x, pw):
    flat = tuple((v for pair in reversed(pw) for v in pair))
    return torch.nn.functional.pad(x, flat)
kernel_name = 'adaLN_cond__softmax_full_mha__glu_gated_glu__prompt'

def setup_inputs():

    _w = lambda a: (lambda t: t.to(torch.bfloat16) if t.is_floating_point() else t)(torch.as_tensor(a))

    def _A_setup():
        B, S, D = (1, 2048, 576)
        return {'x': _w((lambda *s: torch.randn(*s, dtype=torch.bfloat16) * 0.05)(B, S, D)), 'wqkv': _w((lambda *s: torch.randn(*s, dtype=torch.bfloat16) * 0.05)(D, 3 * D)), 'wo': _w((lambda *s: torch.randn(*s, dtype=torch.bfloat16) * 0.05)(D, D))}
    _A_in = _A_setup()

    def _B_setup():
        B, S, D, F = (1, 2048, 576, 4608)
        return {'x': _w((lambda *s: torch.randn(*s, dtype=torch.bfloat16) * 0.05)(B, S, D)), 'w_gate': _w((lambda *s: torch.randn(*s, dtype=torch.bfloat16) * 0.05)(D, F)), 'w_up': _w((lambda *s: torch.randn(*s, dtype=torch.bfloat16) * 0.05)(D, F)), 'w_down': _w((lambda *s: torch.randn(*s, dtype=torch.bfloat16) * 0.05)(F, D))}
    _B_in = _B_setup()
    return {'A_x': _A_in['x'], 'A_wqkv': _A_in['wqkv'], 'A_wo': _A_in['wo'], 'B_x': _B_in['x'], 'B_w_gate': _B_in['w_gate'], 'B_w_up': _B_in['w_up'], 'B_w_down': _B_in['w_down'], 'c': _w((lambda *s: torch.randn(*s, dtype=torch.bfloat16) * 0.1)(1, 576) * 8.0), 'w_mod': _w((lambda *s: torch.randn(*s, dtype=torch.bfloat16) * 0.1)(576, 6 * 576) * 576 ** (-0.5) * 8.0)}

def reference(A_x, A_wqkv, A_wo, B_x, B_w_gate, B_w_up, B_w_down, c, w_mod):

    def _A_ref(x, wqkv, wo):
        B, S, D = x.shape
        H = 32
        Dh = D // H
        qkv = (lambda x, *d: x.permute(*d))((x @ wqkv).reshape(B, S, 3, H, Dh), 2, 0, 3, 1, 4)
        q, k, v = (qkv[0], qkv[1], qkv[2])
        scale = Dh ** (-0.5)
        scores = torch.einsum('bhqd,bhkd->bhqk', q, k) * scale
        p = _softmax(scores, axis=-1)
        o = torch.einsum('bhqk,bhkd->bhqd', p, v)
        return (lambda x, *d: x.permute(*d))(o, 0, 2, 1, 3).reshape(B, S, D) @ wo

    def _B_ref(x, w_gate, w_up, w_down):
        g = torch.einsum('bsd,df->bsf', x, w_gate)
        u = torch.einsum('bsd,df->bsf', x, w_up)
        h = _sigmoid(g) * u
        return torch.einsum('bsf,fd->bsd', h, w_down)
    x = A_x
    mod = (_silu(c) @ w_mod).reshape(c.shape[0], 6, 1, -1)
    sa, ca, ga, sb, cb, gb = (mod[:, 0].clone(), mod[:, 1].clone(), mod[:, 2].clone(), mod[:, 3].clone(), mod[:, 4].clone(), mod[:, 5].clone())
    h = _layernorm(x, axis=-1) * (1 + ca) + sa
    x = x + ga * _A_ref(h, A_wqkv, A_wo)
    h = _layernorm(x, axis=-1) * (1 + cb) + sb
    x = x + gb * _B_ref(h, B_w_gate, B_w_up, B_w_down)
    return x
```

```cpp
#include <cuda_runtime.h>
#include <cuda_bf16.h>
#include <cuda.h>
#include <stdint.h>

typedef __nv_bfloat16 bf16;

constexpr int S_ = 2048, D_ = 576, H_ = 32, F_ = 4608;

__device__ __align__(256) float g_mod[6 * D_];
__device__ __align__(1024) uint4 g_qkvp[3 * H_ * 2 * S_];
__device__ __align__(1024) uint32_t g_qkvx[3 * H_ * S_];
__device__ __align__(1024) bf16 g_o[S_ * D_];
__device__ __align__(1024) bf16 g_x1[S_ * D_];
__device__ __align__(128) float2 g_stat[S_ * 8];
__device__ unsigned g_flag_x1[16 * 32];
__device__ __align__(1024) uint4 g_part[16 * 8 * 8 * 1024];
__device__ __align__(1024) uint4 g_part8[16 * 8 * 8 * 128];
__device__ __align__(1024) uint4 g_last[16 * 8 * 4 * 1024];
__device__ uint4 g_tab1[144];
__device__ __align__(16) uint4 g_tab2[144];
__device__ unsigned g_flag_p8[16 * 8 * 32];

__device__ __forceinline__ uint32_t smem_u32(const void* p) { return (uint32_t)__cvta_generic_to_shared(p); }
__device__ __forceinline__ void mbar_init(uint32_t a, int c) { asm volatile("mbarrier.init.shared::cta.b64 [%0], %1;" ::"r"(a), "r"(c) : "memory"); }
__device__ __forceinline__ void mbar_expect(uint32_t a, int bytes) { asm volatile("mbarrier.arrive.expect_tx.shared::cta.b64 _, [%0], %1;" ::"r"(a), "r"(bytes) : "memory"); }
__device__ __forceinline__ void mbar_arrive(uint32_t a) { asm volatile("mbarrier.arrive.shared::cta.b64 _, [%0];" ::"r"(a) : "memory"); }
__device__ __forceinline__ bool mbar_try(uint32_t a, int par) {
  uint32_t ok;
  asm volatile("{\n.reg .pred p;\nmbarrier.try_wait.parity.shared::cta.b64 p, [%1], %2;\nselp.u32 %0, 1, 0, p;\n}" : "=r"(ok) : "r"(a), "r"(par) : "memory");
  return ok;
}
__device__ __forceinline__ void mbar_wait_c(uint32_t a, int par) {
#pragma unroll 1
  for (int it = 0; it < (1 << 22); it++) if (mbar_try(a, par)) break;
}
__device__ __forceinline__ void mbar_wait(uint32_t a, int par) {
  if (mbar_try(a, par)) return;
#pragma unroll 1
  for (int it = 0; it < (1 << 22); it++) if (mbar_try(a, par)) break;
}
__device__ __forceinline__ void tma2d(uint32_t dst, const CUtensorMap* m, int c0, int c1, uint32_t bar) {
  asm volatile("cp.async.bulk.tensor.2d.shared::cluster.global.mbarrier::complete_tx::bytes [%0], [%1, {%3, %4}], [%2];"
               ::"r"(dst), "l"(m), "r"(bar), "r"(c0), "r"(c1) : "memory");
}
__device__ __forceinline__ void bulk_g2s(uint32_t dst, const void* src, int bytes, uint32_t bar) {
  asm volatile("cp.async.bulk.shared::cluster.global.mbarrier::complete_tx::bytes [%0], [%1], %2, [%3];"
               ::"r"(dst), "l"(src), "r"(bytes), "r"(bar) : "memory");
}
__device__ __forceinline__ void bulk_s2g(void* dst, uint32_t src, int bytes) {
  asm volatile("cp.async.bulk.global.shared::cta.bulk_group [%0], [%1], %2;" ::"l"(dst), "r"(src), "r"(bytes) : "memory");
}
__device__ __forceinline__ void bulk_commit() { asm volatile("cp.async.bulk.commit_group;" ::: "memory"); }
__device__ __forceinline__ void bulk_wait0() { asm volatile("cp.async.bulk.wait_group 0;" ::: "memory"); }
__device__ __forceinline__ void l2_prefetch(const void* p, int bytes) { asm volatile("cp.async.bulk.prefetch.L2.global [%0], %1;" ::"l"(p), "r"(bytes) : "memory"); }
__device__ __forceinline__ void fence_async_smem() { asm volatile("fence.proxy.async.shared::cta;" ::: "memory"); }
__device__ __forceinline__ void fence_async_all() { asm volatile("fence.proxy.async;" ::: "memory"); }
__device__ __forceinline__ void named_bar(int id, int n) { asm volatile("bar.sync %0, %1;" ::"r"(id), "r"(n) : "memory"); }
__device__ __forceinline__ void named_arrive(int id, int n) { asm volatile("bar.arrive %0, %1;" ::"r"(id), "r"(n) : "memory"); }
__device__ __forceinline__ void pdl_wait() { asm volatile("griddepcontrol.wait;" ::: "memory"); }
__device__ __forceinline__ void pdl_launch() { asm volatile("griddepcontrol.launch_dependents;" ::: "memory"); }
__device__ __forceinline__ void prefetch_tmap(const CUtensorMap* m) { asm volatile("prefetch.tensormap [%0];" ::"l"(m) : "memory"); }
__device__ __forceinline__ unsigned ld_acquire(const unsigned* p) { unsigned v; asm volatile("ld.acquire.gpu.global.u32 %0, [%1];" : "=r"(v) : "l"(p) : "memory"); return v; }
__device__ __forceinline__ void red_release(unsigned* p, unsigned v) { asm volatile("red.release.gpu.global.add.u32 [%0], %1;" ::"l"(p), "r"(v) : "memory"); }
__device__ __forceinline__ void spin_ge(const unsigned* p, unsigned target) {
#pragma unroll 1
  for (int it = 0; it < (1 << 20); it++) { if (ld_acquire(p) >= target) break; __nanosleep(64); }
}
template <int R> __device__ __forceinline__ void reg_alloc() { asm volatile("setmaxnreg.inc.sync.aligned.u32 %0;" ::"n"(R)); }
template <int R> __device__ __forceinline__ void reg_dealloc() { asm volatile("setmaxnreg.dec.sync.aligned.u32 %0;" ::"n"(R)); }
__device__ __forceinline__ void wg_fence() { asm volatile("wgmma.fence.sync.aligned;" ::: "memory"); }
__device__ __forceinline__ void wg_commit() { asm volatile("wgmma.commit_group.sync.aligned;" ::: "memory"); }
template <int N> __device__ __forceinline__ void wg_wait() { asm volatile("wgmma.wait_group.sync.aligned %0;" ::"n"(N) : "memory"); }
__device__ __forceinline__ uint64_t mkdesc(uint32_t addr, uint32_t lbo, uint32_t sbo, uint32_t sw) {
  return (uint64_t)((addr & 0x3FFFF) >> 4) | ((uint64_t)(lbo >> 4) << 16) | ((uint64_t)(sbo >> 4) << 32) | ((uint64_t)sw << 62);
}
template <int N> __device__ __forceinline__ void fence_regs(float (&d)[N]) {
#pragma unroll
  for (int i = 0; i < N; i++) asm volatile("" : "+f"(d[i])::"memory");
}
template <int N> __device__ __forceinline__ void fence_regs(uint32_t (&d)[N]) {
#pragma unroll
  for (int i = 0; i < N; i++) asm volatile("" : "+r"(d[i])::"memory");
}
__device__ __forceinline__ void ldsm4(uint32_t& a, uint32_t& b, uint32_t& c, uint32_t& d, uint32_t addr) {
  asm volatile("ldmatrix.sync.aligned.m8n8.x4.shared.b16 {%0,%1,%2,%3}, [%4];" : "=r"(a), "=r"(b), "=r"(c), "=r"(d) : "r"(addr) : "memory");
}
__device__ __forceinline__ uint4 lds128(uint32_t a) { uint4 v; asm volatile("ld.shared.v4.u32 {%0,%1,%2,%3}, [%4];" : "=r"(v.x), "=r"(v.y), "=r"(v.z), "=r"(v.w) : "r"(a) : "memory"); return v; }
__device__ __forceinline__ uint32_t lds32(uint32_t a) { uint32_t v; asm volatile("ld.shared.u32 %0, [%1];" : "=r"(v) : "r"(a) : "memory"); return v; }
__device__ __forceinline__ void sts128(uint32_t a, uint32_t x, uint32_t y, uint32_t z, uint32_t w) { asm volatile("st.shared.v4.u32 [%0], {%1,%2,%3,%4};" ::"r"(a), "r"(x), "r"(y), "r"(z), "r"(w) : "memory"); }
__device__ __forceinline__ void sts32(uint32_t a, uint32_t x) { asm volatile("st.shared.u32 [%0], %1;" ::"r"(a), "r"(x) : "memory"); }
__device__ __forceinline__ uint32_t packbf(float lo, float hi) { uint32_t r; asm("cvt.rn.bf16x2.f32 %0, %1, %2;" : "=r"(r) : "f"(hi), "f"(lo)); return r; }
__device__ __forceinline__ float bflo(uint32_t v) { return __uint_as_float(v << 16); }
__device__ __forceinline__ float bfhi(uint32_t v) { return __uint_as_float(v & 0xFFFF0000u); }
__device__ __forceinline__ float bfround(float x) { return __bfloat162float(__float2bfloat16_rn(x)); }
__device__ __forceinline__ uint32_t fma_bf2(uint32_t a, uint32_t b, uint32_t c) { uint32_t r; asm("fma.rn.bf16x2 %0, %1, %2, %3;" : "=r"(r) : "r"(a), "r"(b), "r"(c)); return r; }
__device__ __forceinline__ uint32_t fma_h2(uint32_t a, uint32_t b, uint32_t c) { uint32_t r; asm("fma.rn.f16x2 %0, %1, %2, %3;" : "=r"(r) : "r"(a), "r"(b), "r"(c)); return r; }
__device__ __forceinline__ float ex2f(float x) { float y; asm("ex2.approx.ftz.f32 %0, %1;" : "=f"(y) : "f"(x)); return y; }
__device__ __forceinline__ float tanhf_(float x) { float y; asm("tanh.approx.f32 %0, %1;" : "=f"(y) : "f"(x)); return y; }

__device__ __forceinline__ void bulk_wait0_read() { asm volatile("cp.async.bulk.wait_group.read 0;" ::: "memory"); }
__device__ __forceinline__ void tma_store2d(const CUtensorMap* m, int c0, int c1, uint32_t src) {
  asm volatile("cp.async.bulk.tensor.2d.global.shared::cta.bulk_group [%0, {%2, %3}], [%1];" ::"l"(m), "r"(src), "r"(c0), "r"(c1) : "memory");
}
__device__ __forceinline__ void stsm4(uint32_t addr, uint32_t a, uint32_t b, uint32_t c, uint32_t d) {
  asm volatile("stmatrix.sync.aligned.m8n8.x4.shared.b16 [%0], {%1,%2,%3,%4};" ::"r"(addr), "r"(a), "r"(b), "r"(c), "r"(d) : "memory");
}
__device__ __forceinline__ void hmma(float (&c)[4], const uint32_t* a, uint32_t b0, uint32_t b1) {
  asm("mma.sync.aligned.m16n8k16.row.col.f32.bf16.bf16.f32 {%0,%1,%2,%3}, {%4,%5,%6,%7}, {%8,%9}, {%0,%1,%2,%3};"
      : "+f"(c[0]), "+f"(c[1]), "+f"(c[2]), "+f"(c[3]) : "r"(a[0]), "r"(a[1]), "r"(a[2]), "r"(a[3]), "r"(b0), "r"(b1));
}
__device__ __forceinline__ void hmma8(float (&c)[4], uint32_t a0, uint32_t a1, uint32_t b) {
  asm("mma.sync.aligned.m16n8k8.row.col.f32.bf16.bf16.f32 {%0,%1,%2,%3}, {%4,%5}, {%6}, {%0,%1,%2,%3};"
      : "+f"(c[0]), "+f"(c[1]), "+f"(c[2]), "+f"(c[3]) : "r"(a0), "r"(a1), "r"(b));
}
__device__ __forceinline__ void tma2d_mc(uint32_t dst, const CUtensorMap* m, int c0, int c1, uint32_t bar) {
  asm volatile("cp.async.bulk.tensor.2d.shared::cluster.global.mbarrier::complete_tx::bytes.multicast::cluster [%0], [%1, {%3, %4}], [%2], %5;"
               ::"r"(dst), "l"(m), "r"(bar), "r"(c0), "r"(c1), "h"((uint16_t)3) : "memory");
}
__device__ __forceinline__ void tma3d(uint32_t dst, const CUtensorMap* m, int c0, int c1, int c2, uint32_t bar) {
  asm volatile("cp.async.bulk.tensor.3d.shared::cluster.global.mbarrier::complete_tx::bytes [%0], [%1, {%3, %4, %5}], [%2];"
               ::"r"(dst), "l"(m), "r"(bar), "r"(c0), "r"(c1), "r"(c2) : "memory");
}
__device__ __forceinline__ void tma3d_mc(uint32_t dst, const CUtensorMap* m, int c0, int c1, int c2, uint32_t bar) {
  asm volatile("cp.async.bulk.tensor.3d.shared::cluster.global.mbarrier::complete_tx::bytes.multicast::cluster [%0], [%1, {%3, %4, %5}], [%2], %6;"
               ::"r"(dst), "l"(m), "r"(bar), "r"(c0), "r"(c1), "r"(c2), "h"((uint16_t)3) : "memory");
}
__device__ __forceinline__ uint32_t mapa(uint32_t a, int rank) { uint32_t r; asm("mapa.shared::cluster.u32 %0, %1, %2;" : "=r"(r) : "r"(a), "r"(rank)); return r; }
__device__ __forceinline__ void mbar_arrive_cl(uint32_t a) { asm volatile("mbarrier.arrive.shared::cluster.b64 _, [%0];" ::"r"(a) : "memory"); }
__device__ __forceinline__ void cluster_sync() {
  asm volatile("barrier.cluster.arrive.relaxed;\nbarrier.cluster.wait;" ::: "memory");
}
#define TX(w, i)
#define TS(k, i)
#define TC(k, i)
__device__ __forceinline__ void wgmma_rs_n128_t1(float (&d)[64], uint32_t a0, uint32_t a1, uint32_t a2, uint32_t a3, uint64_t db, int sc) {
  asm volatile("{\n.reg .pred p;\nsetp.ne.b32 p, %69, 0;\n"
    "wgmma.mma_async.sync.aligned.m64n128k16.f32.bf16.bf16 {%0, %1, %2, %3, %4, %5, %6, %7, %8, %9, %10, %11, %12, %13, %14, %15, %16, %17, %18, %19, %20, %21, %22, %23, %24, %25, %26, %27, %28, %29, %30, %31, %32, %33, %34, %35, %36, %37, %38, %39, %40, %41, %42, %43, %44, %45, %46, %47, %48, %49, %50, %51, %52, %53, %54, %55, %56, %57, %58, %59, %60, %61, %62, %63}, {%64, %65, %66, %67}, %68, p, 1, 1, 1;\n}\n"
    : "+f"(d[0]), "+f"(d[1]), "+f"(d[2]), "+f"(d[3]), "+f"(d[4]), "+f"(d[5]), "+f"(d[6]), "+f"(d[7]), "+f"(d[8]), "+f"(d[9]), "+f"(d[10]), "+f"(d[11]), "+f"(d[12]), "+f"(d[13]), "+f"(d[14]), "+f"(d[15]), "+f"(d[16]), "+f"(d[17]), "+f"(d[18]), "+f"(d[19]), "+f"(d[20]), "+f"(d[21]), "+f"(d[22]), "+f"(d[23]), "+f"(d[24]), "+f"(d[25]), "+f"(d[26]), "+f"(d[27]), "+f"(d[28]), "+f"(d[29]), "+f"(d[30]), "+f"(d[31]), "+f"(d[32]), "+f"(d[33]), "+f"(d[34]), "+f"(d[35]), "+f"(d[36]), "+f"(d[37]), "+f"(d[38]), "+f"(d[39]), "+f"(d[40]), "+f"(d[41]), "+f"(d[42]), "+f"(d[43]), "+f"(d[44]), "+f"(d[45]), "+f"(d[46]), "+f"(d[47]), "+f"(d[48]), "+f"(d[49]), "+f"(d[50]), "+f"(d[51]), "+f"(d[52]), "+f"(d[53]), "+f"(d[54]), "+f"(d[55]), "+f"(d[56]), "+f"(d[57]), "+f"(d[58]), "+f"(d[59]), "+f"(d[60]), "+f"(d[61]), "+f"(d[62]), "+f"(d[63])
    : "r"(a0), "r"(a1), "r"(a2), "r"(a3), "l"(db), "r"(sc));
}
__device__ __forceinline__ void wgmma_rz_n128_t1(float (&d)[64], uint32_t a0, uint32_t a1, uint32_t a2, uint32_t a3, uint64_t db) {
  asm volatile("{\n.reg .pred p;\nsetp.ne.b32 p, 0, 0;\n"
    "wgmma.mma_async.sync.aligned.m64n128k16.f32.bf16.bf16 {%0, %1, %2, %3, %4, %5, %6, %7, %8, %9, %10, %11, %12, %13, %14, %15, %16, %17, %18, %19, %20, %21, %22, %23, %24, %25, %26, %27, %28, %29, %30, %31, %32, %33, %34, %35, %36, %37, %38, %39, %40, %41, %42, %43, %44, %45, %46, %47, %48, %49, %50, %51, %52, %53, %54, %55, %56, %57, %58, %59, %60, %61, %62, %63}, {%64, %65, %66, %67}, %68, p, 1, 1, 1;\n}\n"
    : "=f"(d[0]), "=f"(d[1]), "=f"(d[2]), "=f"(d[3]), "=f"(d[4]), "=f"(d[5]), "=f"(d[6]), "=f"(d[7]), "=f"(d[8]), "=f"(d[9]), "=f"(d[10]), "=f"(d[11]), "=f"(d[12]), "=f"(d[13]), "=f"(d[14]), "=f"(d[15]), "=f"(d[16]), "=f"(d[17]), "=f"(d[18]), "=f"(d[19]), "=f"(d[20]), "=f"(d[21]), "=f"(d[22]), "=f"(d[23]), "=f"(d[24]), "=f"(d[25]), "=f"(d[26]), "=f"(d[27]), "=f"(d[28]), "=f"(d[29]), "=f"(d[30]), "=f"(d[31]), "=f"(d[32]), "=f"(d[33]), "=f"(d[34]), "=f"(d[35]), "=f"(d[36]), "=f"(d[37]), "=f"(d[38]), "=f"(d[39]), "=f"(d[40]), "=f"(d[41]), "=f"(d[42]), "=f"(d[43]), "=f"(d[44]), "=f"(d[45]), "=f"(d[46]), "=f"(d[47]), "=f"(d[48]), "=f"(d[49]), "=f"(d[50]), "=f"(d[51]), "=f"(d[52]), "=f"(d[53]), "=f"(d[54]), "=f"(d[55]), "=f"(d[56]), "=f"(d[57]), "=f"(d[58]), "=f"(d[59]), "=f"(d[60]), "=f"(d[61]), "=f"(d[62]), "=f"(d[63])
    : "r"(a0), "r"(a1), "r"(a2), "r"(a3), "l"(db));
}
__device__ __forceinline__ void wgmma_rz_n88_t1(float (&d)[44], uint32_t a0, uint32_t a1, uint32_t a2, uint32_t a3, uint64_t db) {
  asm volatile("{\n.reg .pred p;\nsetp.ne.b32 p, 0, 0;\n"
    "wgmma.mma_async.sync.aligned.m64n88k16.f32.bf16.bf16 {%0, %1, %2, %3, %4, %5, %6, %7, %8, %9, %10, %11, %12, %13, %14, %15, %16, %17, %18, %19, %20, %21, %22, %23, %24, %25, %26, %27, %28, %29, %30, %31, %32, %33, %34, %35, %36, %37, %38, %39, %40, %41, %42, %43}, {%44, %45, %46, %47}, %48, p, 1, 1, 1;\n}\n"
    : "=f"(d[0]), "=f"(d[1]), "=f"(d[2]), "=f"(d[3]), "=f"(d[4]), "=f"(d[5]), "=f"(d[6]), "=f"(d[7]), "=f"(d[8]), "=f"(d[9]), "=f"(d[10]), "=f"(d[11]), "=f"(d[12]), "=f"(d[13]), "=f"(d[14]), "=f"(d[15]), "=f"(d[16]), "=f"(d[17]), "=f"(d[18]), "=f"(d[19]), "=f"(d[20]), "=f"(d[21]), "=f"(d[22]), "=f"(d[23]), "=f"(d[24]), "=f"(d[25]), "=f"(d[26]), "=f"(d[27]), "=f"(d[28]), "=f"(d[29]), "=f"(d[30]), "=f"(d[31]), "=f"(d[32]), "=f"(d[33]), "=f"(d[34]), "=f"(d[35]), "=f"(d[36]), "=f"(d[37]), "=f"(d[38]), "=f"(d[39]), "=f"(d[40]), "=f"(d[41]), "=f"(d[42]), "=f"(d[43])
    : "r"(a0), "r"(a1), "r"(a2), "r"(a3), "l"(db));
}
__device__ __forceinline__ void wgmma_rz_n64_t1(float (&d)[32], uint32_t a0, uint32_t a1, uint32_t a2, uint32_t a3, uint64_t db) {
  asm volatile("{\n.reg .pred p;\nsetp.ne.b32 p, 0, 0;\n"
    "wgmma.mma_async.sync.aligned.m64n64k16.f32.bf16.bf16 {%0, %1, %2, %3, %4, %5, %6, %7, %8, %9, %10, %11, %12, %13, %14, %15, %16, %17, %18, %19, %20, %21, %22, %23, %24, %25, %26, %27, %28, %29, %30, %31}, {%32, %33, %34, %35}, %36, p, 1, 1, 1;\n}\n"
    : "=f"(d[0]), "=f"(d[1]), "=f"(d[2]), "=f"(d[3]), "=f"(d[4]), "=f"(d[5]), "=f"(d[6]), "=f"(d[7]), "=f"(d[8]), "=f"(d[9]), "=f"(d[10]), "=f"(d[11]), "=f"(d[12]), "=f"(d[13]), "=f"(d[14]), "=f"(d[15]), "=f"(d[16]), "=f"(d[17]), "=f"(d[18]), "=f"(d[19]), "=f"(d[20]), "=f"(d[21]), "=f"(d[22]), "=f"(d[23]), "=f"(d[24]), "=f"(d[25]), "=f"(d[26]), "=f"(d[27]), "=f"(d[28]), "=f"(d[29]), "=f"(d[30]), "=f"(d[31])
    : "r"(a0), "r"(a1), "r"(a2), "r"(a3), "l"(db));
}
__device__ __forceinline__ void wgmma_rz_n128_t0(float (&d)[64], uint32_t a0, uint32_t a1, uint32_t a2, uint32_t a3, uint64_t db) {
  asm volatile("{\n.reg .pred p;\nsetp.ne.b32 p, 0, 0;\n"
    "wgmma.mma_async.sync.aligned.m64n128k16.f32.bf16.bf16 {%0, %1, %2, %3, %4, %5, %6, %7, %8, %9, %10, %11, %12, %13, %14, %15, %16, %17, %18, %19, %20, %21, %22, %23, %24, %25, %26, %27, %28, %29, %30, %31, %32, %33, %34, %35, %36, %37, %38, %39, %40, %41, %42, %43, %44, %45, %46, %47, %48, %49, %50, %51, %52, %53, %54, %55, %56, %57, %58, %59, %60, %61, %62, %63}, {%64, %65, %66, %67}, %68, p, 1, 1, 0;\n}\n"
    : "=f"(d[0]), "=f"(d[1]), "=f"(d[2]), "=f"(d[3]), "=f"(d[4]), "=f"(d[5]), "=f"(d[6]), "=f"(d[7]), "=f"(d[8]), "=f"(d[9]), "=f"(d[10]), "=f"(d[11]), "=f"(d[12]), "=f"(d[13]), "=f"(d[14]), "=f"(d[15]), "=f"(d[16]), "=f"(d[17]), "=f"(d[18]), "=f"(d[19]), "=f"(d[20]), "=f"(d[21]), "=f"(d[22]), "=f"(d[23]), "=f"(d[24]), "=f"(d[25]), "=f"(d[26]), "=f"(d[27]), "=f"(d[28]), "=f"(d[29]), "=f"(d[30]), "=f"(d[31]), "=f"(d[32]), "=f"(d[33]), "=f"(d[34]), "=f"(d[35]), "=f"(d[36]), "=f"(d[37]), "=f"(d[38]), "=f"(d[39]), "=f"(d[40]), "=f"(d[41]), "=f"(d[42]), "=f"(d[43]), "=f"(d[44]), "=f"(d[45]), "=f"(d[46]), "=f"(d[47]), "=f"(d[48]), "=f"(d[49]), "=f"(d[50]), "=f"(d[51]), "=f"(d[52]), "=f"(d[53]), "=f"(d[54]), "=f"(d[55]), "=f"(d[56]), "=f"(d[57]), "=f"(d[58]), "=f"(d[59]), "=f"(d[60]), "=f"(d[61]), "=f"(d[62]), "=f"(d[63])
    : "r"(a0), "r"(a1), "r"(a2), "r"(a3), "l"(db));
}
__device__ __forceinline__ void wgmma_rs_n88_t1(float (&d)[44], uint32_t a0, uint32_t a1, uint32_t a2, uint32_t a3, uint64_t db, int sc) {
  asm volatile("{\n.reg .pred p;\nsetp.ne.b32 p, %49, 0;\n"
    "wgmma.mma_async.sync.aligned.m64n88k16.f32.bf16.bf16 {%0, %1, %2, %3, %4, %5, %6, %7, %8, %9, %10, %11, %12, %13, %14, %15, %16, %17, %18, %19, %20, %21, %22, %23, %24, %25, %26, %27, %28, %29, %30, %31, %32, %33, %34, %35, %36, %37, %38, %39, %40, %41, %42, %43}, {%44, %45, %46, %47}, %48, p, 1, 1, 1;\n}\n"
    : "+f"(d[0]), "+f"(d[1]), "+f"(d[2]), "+f"(d[3]), "+f"(d[4]), "+f"(d[5]), "+f"(d[6]), "+f"(d[7]), "+f"(d[8]), "+f"(d[9]), "+f"(d[10]), "+f"(d[11]), "+f"(d[12]), "+f"(d[13]), "+f"(d[14]), "+f"(d[15]), "+f"(d[16]), "+f"(d[17]), "+f"(d[18]), "+f"(d[19]), "+f"(d[20]), "+f"(d[21]), "+f"(d[22]), "+f"(d[23]), "+f"(d[24]), "+f"(d[25]), "+f"(d[26]), "+f"(d[27]), "+f"(d[28]), "+f"(d[29]), "+f"(d[30]), "+f"(d[31]), "+f"(d[32]), "+f"(d[33]), "+f"(d[34]), "+f"(d[35]), "+f"(d[36]), "+f"(d[37]), "+f"(d[38]), "+f"(d[39]), "+f"(d[40]), "+f"(d[41]), "+f"(d[42]), "+f"(d[43])
    : "r"(a0), "r"(a1), "r"(a2), "r"(a3), "l"(db), "r"(sc));
}
__device__ __forceinline__ void wgmma_rs_n64_t1(float (&d)[32], uint32_t a0, uint32_t a1, uint32_t a2, uint32_t a3, uint64_t db, int sc) {
  asm volatile("{\n.reg .pred p;\nsetp.ne.b32 p, %37, 0;\n"
    "wgmma.mma_async.sync.aligned.m64n64k16.f32.bf16.bf16 {%0, %1, %2, %3, %4, %5, %6, %7, %8, %9, %10, %11, %12, %13, %14, %15, %16, %17, %18, %19, %20, %21, %22, %23, %24, %25, %26, %27, %28, %29, %30, %31}, {%32, %33, %34, %35}, %36, p, 1, 1, 1;\n}\n"
    : "+f"(d[0]), "+f"(d[1]), "+f"(d[2]), "+f"(d[3]), "+f"(d[4]), "+f"(d[5]), "+f"(d[6]), "+f"(d[7]), "+f"(d[8]), "+f"(d[9]), "+f"(d[10]), "+f"(d[11]), "+f"(d[12]), "+f"(d[13]), "+f"(d[14]), "+f"(d[15]), "+f"(d[16]), "+f"(d[17]), "+f"(d[18]), "+f"(d[19]), "+f"(d[20]), "+f"(d[21]), "+f"(d[22]), "+f"(d[23]), "+f"(d[24]), "+f"(d[25]), "+f"(d[26]), "+f"(d[27]), "+f"(d[28]), "+f"(d[29]), "+f"(d[30]), "+f"(d[31])
    : "r"(a0), "r"(a1), "r"(a2), "r"(a3), "l"(db), "r"(sc));
}
__device__ __forceinline__ void wgmma_rs_n128_t0(float (&d)[64], uint32_t a0, uint32_t a1, uint32_t a2, uint32_t a3, uint64_t db, int sc) {
  asm volatile("{\n.reg .pred p;\nsetp.ne.b32 p, %69, 0;\n"
    "wgmma.mma_async.sync.aligned.m64n128k16.f32.bf16.bf16 {%0, %1, %2, %3, %4, %5, %6, %7, %8, %9, %10, %11, %12, %13, %14, %15, %16, %17, %18, %19, %20, %21, %22, %23, %24, %25, %26, %27, %28, %29, %30, %31, %32, %33, %34, %35, %36, %37, %38, %39, %40, %41, %42, %43, %44, %45, %46, %47, %48, %49, %50, %51, %52, %53, %54, %55, %56, %57, %58, %59, %60, %61, %62, %63}, {%64, %65, %66, %67}, %68, p, 1, 1, 0;\n}\n"
    : "+f"(d[0]), "+f"(d[1]), "+f"(d[2]), "+f"(d[3]), "+f"(d[4]), "+f"(d[5]), "+f"(d[6]), "+f"(d[7]), "+f"(d[8]), "+f"(d[9]), "+f"(d[10]), "+f"(d[11]), "+f"(d[12]), "+f"(d[13]), "+f"(d[14]), "+f"(d[15]), "+f"(d[16]), "+f"(d[17]), "+f"(d[18]), "+f"(d[19]), "+f"(d[20]), "+f"(d[21]), "+f"(d[22]), "+f"(d[23]), "+f"(d[24]), "+f"(d[25]), "+f"(d[26]), "+f"(d[27]), "+f"(d[28]), "+f"(d[29]), "+f"(d[30]), "+f"(d[31]), "+f"(d[32]), "+f"(d[33]), "+f"(d[34]), "+f"(d[35]), "+f"(d[36]), "+f"(d[37]), "+f"(d[38]), "+f"(d[39]), "+f"(d[40]), "+f"(d[41]), "+f"(d[42]), "+f"(d[43]), "+f"(d[44]), "+f"(d[45]), "+f"(d[46]), "+f"(d[47]), "+f"(d[48]), "+f"(d[49]), "+f"(d[50]), "+f"(d[51]), "+f"(d[52]), "+f"(d[53]), "+f"(d[54]), "+f"(d[55]), "+f"(d[56]), "+f"(d[57]), "+f"(d[58]), "+f"(d[59]), "+f"(d[60]), "+f"(d[61]), "+f"(d[62]), "+f"(d[63])
    : "r"(a0), "r"(a1), "r"(a2), "r"(a3), "l"(db), "r"(sc));
}
__device__ __forceinline__ void wgmma_rs_n24_t1(float (&d)[12], uint32_t a0, uint32_t a1, uint32_t a2, uint32_t a3, uint64_t db, int sc) {
  asm volatile("{\n.reg .pred p;\nsetp.ne.b32 p, %17, 0;\n"
    "wgmma.mma_async.sync.aligned.m64n24k16.f32.bf16.bf16 {%0, %1, %2, %3, %4, %5, %6, %7, %8, %9, %10, %11}, {%12, %13, %14, %15}, %16, p, 1, 1, 1;\n}\n"
    : "+f"(d[0]), "+f"(d[1]), "+f"(d[2]), "+f"(d[3]), "+f"(d[4]), "+f"(d[5]), "+f"(d[6]), "+f"(d[7]), "+f"(d[8]), "+f"(d[9]), "+f"(d[10]), "+f"(d[11])
    : "r"(a0), "r"(a1), "r"(a2), "r"(a3), "l"(db), "r"(sc));
}
__device__ __forceinline__ void wgmma_ss_n72_t1(float (&d)[36], uint64_t da, uint64_t db, int sc) {
  asm volatile("{\n.reg .pred p;\nsetp.ne.b32 p, %38, 0;\n"
    "wgmma.mma_async.sync.aligned.m64n72k16.f32.bf16.bf16 {%0, %1, %2, %3, %4, %5, %6, %7, %8, %9, %10, %11, %12, %13, %14, %15, %16, %17, %18, %19, %20, %21, %22, %23, %24, %25, %26, %27, %28, %29, %30, %31, %32, %33, %34, %35}, %36, %37, p, 1, 1, 0, 1;\n}\n"
    : "+f"(d[0]), "+f"(d[1]), "+f"(d[2]), "+f"(d[3]), "+f"(d[4]), "+f"(d[5]), "+f"(d[6]), "+f"(d[7]), "+f"(d[8]), "+f"(d[9]), "+f"(d[10]), "+f"(d[11]), "+f"(d[12]), "+f"(d[13]), "+f"(d[14]), "+f"(d[15]), "+f"(d[16]), "+f"(d[17]), "+f"(d[18]), "+f"(d[19]), "+f"(d[20]), "+f"(d[21]), "+f"(d[22]), "+f"(d[23]), "+f"(d[24]), "+f"(d[25]), "+f"(d[26]), "+f"(d[27]), "+f"(d[28]), "+f"(d[29]), "+f"(d[30]), "+f"(d[31]), "+f"(d[32]), "+f"(d[33]), "+f"(d[34]), "+f"(d[35])
    : "l"(da), "l"(db), "r"(sc));
}

constexpr int XBYTES = 9 * 16384;
constexpr int NST = 5;
constexpr int AUX_OFF = XBYTES + NST * 16384;
constexpr int BAR_OFF = AUX_OFF + 2304;
constexpr int GB_OFF = BAR_OFF + 256;
constexpr int SMEM_GEMM = GB_OFF + 512;

constexpr int XR_OFF = 7 * 16384;
struct XRing { int st; uint32_t ph; };
__device__ __forceinline__ void xr_next(XRing& r, int lo) {
  r.ph ^= 1u << r.st;
  if (++r.st == 7) r.st = 0;
  if (r.st < lo) r.st = lo;
}

__device__ __forceinline__ void mod_load(uint4 (&w)[5], const bf16* __restrict__ wmod, int c0, int tid) {
  const bf16* p = wmod + (size_t)(tid >> 1) * (6 * D_) + c0 + (tid & 1) * 8;
#pragma unroll
  for (int i = 0; i < 5; i++)
    w[i] = (i < 4 || tid < 128) ? __ldg(reinterpret_cast<const uint4*>(p + (size_t)128 * i * (6 * D_))) : make_uint4(0, 0, 0, 0);
}
__device__ __forceinline__ float mod_finish(const uint4 (&w)[5], const bf16* c, int tid, float* red, int barid) {
  float sc[5];
#pragma unroll
  for (int i = 0; i < 5; i++) sc[i] = (i < 4 || tid < 128) ? __bfloat162float(c[(tid >> 1) + 128 * i]) : 0.f;
  float acc[8];
#pragma unroll
  for (int e = 0; e < 8; e++) acc[e] = 0.f;
#pragma unroll
  for (int i = 0; i < 5; i++) {
    const float f = bfround(__fdividef(sc[i], 1.f + __expf(-sc[i])));
    acc[0] += f * bflo(w[i].x); acc[1] += f * bfhi(w[i].x); acc[2] += f * bflo(w[i].y); acc[3] += f * bfhi(w[i].y);
    acc[4] += f * bflo(w[i].z); acc[5] += f * bfhi(w[i].z); acc[6] += f * bflo(w[i].w); acc[7] += f * bfhi(w[i].w);
  }
#pragma unroll
  for (int e = 0; e < 8; e++)
#pragma unroll
    for (int o = 2; o < 32; o *= 2) acc[e] += __shfl_xor_sync(0xffffffffu, acc[e], o);
  if ((tid & 31) < 2) {
#pragma unroll
    for (int e = 0; e < 8; e++) red[(tid >> 5) * 16 + (tid & 1) * 8 + e] = acc[e];
  }
  named_bar(barid, 256);
  float s = 0.f;
  if (tid < 32) {
#pragma unroll
    for (int w8 = 0; w8 < 8; w8++) s += red[w8 * 16 + (tid & 15)];
  }
  return bfround(s);
}
__device__ __forceinline__ void store_table(uint4* dst, float s, bool scale, float mul, uint32_t inv, int lane) {
  if (scale) s = bfround(1.f + s);
  s *= mul;
  const uint32_t pr = packbf(s, __shfl_down_sync(0xffffffffu, s, 1)) ^ inv;
  const uint2 e = make_uint2(__shfl_sync(0xffffffffu, pr, (lane & 3) * 2), __shfl_sync(0xffffffffu, pr, 8 + (lane & 3) * 2));
  if (lane < 4) __stcg(reinterpret_cast<uint2*>(dst + lane) + (scale ? 0 : 1), e);
}

__device__ __forceinline__ void load_afrags(uint32_t* a, uint32_t xbase, int kb, int warp8, int lane) {
  const uint32_t rb = xbase + (warp8 * 16 + (lane & 15)) * 128 + kb * 16384;
#pragma unroll
  for (int ks = 0; ks < 4; ks++)
    ldsm4(a[4 * ks], a[4 * ks + 1], a[4 * ks + 2], a[4 * ks + 3], rb + (((ks * 2 + (lane >> 4)) ^ (lane & 7)) << 4));
}
constexpr uint32_t ONE2 = 0x3F803F80u;
__device__ __forceinline__ void center_afrags(uint32_t* a, uint32_t p0, uint32_t p1) {
#pragma unroll
  for (int i = 0; i < 8; i++) { a[2 * i] = fma_bf2(a[2 * i], ONE2, p0); a[2 * i + 1] = fma_bf2(a[2 * i + 1], ONE2, p1); }
}
struct Norm { uint32_t ra, rb, ba, bb; };
__device__ __forceinline__ Norm make_norm(float d0, float r0, float d1, float r1) {
  return Norm{packbf(r0, r0), packbf(r1, r1), packbf(-d0 * r0, -d0 * r0), packbf(-d1 * r1, -d1 * r1)};
}
__device__ __forceinline__ void modulate_afrags(uint32_t* a, uint32_t tab, int kb, const Norm& n) {
#pragma unroll
  for (int ks = 0; ks < 4; ks++) {
    uint4 m = lds128(tab + (kb * 4 + ks) * 64);
    a[4 * ks] = fma_bf2(fma_bf2(a[4 * ks], n.ra, n.ba), m.x, m.z);
    a[4 * ks + 1] = fma_bf2(fma_bf2(a[4 * ks + 1], n.rb, n.bb), m.x, m.z);
    a[4 * ks + 2] = fma_bf2(fma_bf2(a[4 * ks + 2], n.ra, n.ba), m.y, m.w);
    a[4 * ks + 3] = fma_bf2(fma_bf2(a[4 * ks + 3], n.rb, n.bb), m.y, m.w);
  }
}
__device__ __forceinline__ void mma_rs(float (&d)[64], const uint32_t* a, uint64_t db, int sc) {
  if (sc) wgmma_rs_n128_t1(d, a[0], a[1], a[2], a[3], db, 1); else wgmma_rz_n128_t1(d, a[0], a[1], a[2], a[3], db);
}
__device__ __forceinline__ void mma_rs(float (&d)[44], const uint32_t* a, uint64_t db, int sc) {
  if (sc) wgmma_rs_n88_t1(d, a[0], a[1], a[2], a[3], db, 1); else wgmma_rz_n88_t1(d, a[0], a[1], a[2], a[3], db);
}
__device__ __forceinline__ void mma_rs(float (&d)[32], const uint32_t* a, uint64_t db, int sc) {
  if (sc) wgmma_rs_n64_t1(d, a[0], a[1], a[2], a[3], db, 1); else wgmma_rz_n64_t1(d, a[0], a[1], a[2], a[3], db);
}

template <bool CW, int NA, class Pre, class Post>
__device__ __forceinline__ void gemm_tile(float (&acc)[NA], uint32_t (&a)[144], uint32_t ring, uint32_t fullb, uint32_t emptyc,
                                          XRing& r, int lo0, int lo1, int lon, int lane, Pre pre, Post post) {
  int prev = 0;
#pragma unroll
  for (int kb = 0; kb < 9; kb++) {
    pre(kb);
    if (CW) mbar_wait_c(fullb + r.st * 8, (r.ph >> r.st) & 1); else mbar_wait(fullb + r.st * 8, (r.ph >> r.st) & 1);
    const uint64_t db = mkdesc(ring + r.st * 16384, 8192, 1024, 1);
    wg_fence();
#pragma unroll
    for (int ks = 0; ks < 4; ks++) mma_rs(acc, &a[16 * kb + 4 * ks], db + ks * 128, (kb | ks) != 0);
    wg_commit();
    if (kb > 0) { wg_wait<1>(); if (lane < 2) mbar_arrive_cl(emptyc + prev * 8); }
    post(kb);
    prev = r.st;
    xr_next(r, kb < 4 ? lo0 : kb < 8 ? lo1 : lon);
  }
  wg_wait<0>();
  if (lane < 2) mbar_arrive_cl(emptyc + prev * 8);
  fence_regs(acc);
}
#define NOP_HOOK [](int) {}

constexpr float QSCALE = 0.23570226039551584f * 1.4426950408889634f;

template <int NB, int B0, int NA>
__device__ __forceinline__ void qkv_stage_out(const float (&acc)[NA], const uint32_t (&off)[9], int t, int qper) {
#pragma unroll
  for (int b = 0; b < NB; b++) {
    const int per = (B0 + b) / 9, bb = (B0 + b) % 9;
    const float mul = per < qper ? QSCALE : 1.f;
    const uint32_t o0 = off[bb] + per * 4 * 4608;
    const bool ex = (bb == 2 && t == 0) || (bb == 4 && t == 1) || (bb == 6 && t == 2) || (bb == 8 && t == 3);
    sts32(o0, packbf(acc[4 * b] * mul, acc[4 * b + 1] * mul));
    sts32(o0 + (ex ? 32 : 128), packbf(acc[4 * b + 2] * mul, acc[4 * b + 3] * mul));
  }
}

__device__ __forceinline__ void qkv_ship(uint32_t sb, int i, int j, int mb) {
  const int slot = (i * 43) >> 7, p = i - slot * 3, gs = j * 12 + slot;
  void* dst = p < 2 ? (void*)&g_qkvp[(size_t)(gs * 2 + p) * S_ + mb * 128] : (void*)&g_qkvx[(size_t)gs * S_ + mb * 128];
  bulk_s2g(dst, sb + slot * 4608 + p * 2048, p < 2 ? 2048 : 512);
  bulk_commit();
}

__global__ void __launch_bounds__(384, 1)
qkv_kernel(const __grid_constant__ CUtensorMap tm_x, const __grid_constant__ CUtensorMap tm_w,
           const bf16* __restrict__ cvec, const bf16* __restrict__ wmod) {
  extern __shared__ __align__(1024) uint8_t smem[];
  const uint32_t sb = smem_u32(smem);
  const uint32_t fullb = sb + BAR_OFF, emptyb = fullb + 64, xfull = fullb + 128, ep1 = fullb + 56;
  const int tid = threadIdx.x, lane = tid & 31, warp = tid >> 5;
  const int mb = blockIdx.x & 15, j = blockIdx.x >> 4;
  if (warp == 9 && lane * 128 + blockIdx.x < D_) l2_prefetch(wmod + (size_t)(lane * 128 + blockIdx.x) * (6 * D_), 2304);
  if (tid == 256) {
    for (int i = 0; i < 7; i++) { mbar_init(fullb + i * 8, 1); mbar_init(emptyb + i * 8, 16); }
    for (int i = 0; i < 9; i++) mbar_init(xfull + i * 8, 1);
    mbar_init(ep1, 8);
    asm volatile("fence.mbarrier_init.release.cluster;" ::: "memory");
    prefetch_tmap(&tm_w);
    for (int kb = 0; kb < 9; kb++) {
      mbar_expect(xfull + kb * 8, kb ? 16384 : 16384 + 1152);
      if (kb == 0) bulk_g2s(sb + AUX_OFF + 1024, cvec, 1152, xfull);
      tma2d(sb + kb * 16384, &tm_x, kb * 64, mb * 128, xfull + kb * 8);
    }
  }
  __syncwarp();
  cluster_sync();
  pdl_launch();
  if (warp >= 8) {
    reg_dealloc<24>();
    if (warp == 8 && lane == 0) {
      XRing r{2, 0x7Cu};
      const int rank = mb & 1;
#pragma unroll 1
      for (int nt = 0; nt < 2; nt++)
#pragma unroll 1
        for (int kb = 0; kb < 9; kb++) {
          mbar_wait(emptyb + r.st * 8, (r.ph >> r.st) & 1);
          mbar_expect(fullb + r.st * 8, 16384);
          tma3d_mc(sb + XR_OFF + r.st * 16384 + rank * 8192, &tm_w, nt * 128 + rank * 64, j, kb * 64, fullb + r.st * 8);
          xr_next(r, 0);
        }
    } else if (warp == 9) {
      if (lane == 0) g_flag_p8[blockIdx.x * 32] = 0;
      if (lane == 1 && blockIdx.x < 16) g_flag_x1[blockIdx.x * 32] = 0;
      mbar_wait(ep1, 0);
      if (lane < 21) { qkv_ship(sb, lane, j, mb); bulk_wait0_read(); }
    }
  } else {
    reg_alloc<240>();
    TS(0, 0);
    uint4 mw[5];
    const bool domod = blockIdx.x < 72;
    if (domod) mod_load(mw, wmod, blockIdx.x * 16, tid);
    uint32_t a[144];
    TS(0, 1);
    Norm nrm;
    uint32_t cen0, cen1;
    const uint32_t emptyc = mapa(emptyb, lane & 1);
    {
      float c0[4] = {0.f, 0.f, 0.f, 0.f}, c1[4] = {0.f, 0.f, 0.f, 0.f}, c2[4] = {0.f, 0.f, 0.f, 0.f}, c3[4] = {0.f, 0.f, 0.f, 0.f};
#pragma unroll
      for (int kb = 0; kb < 9; kb++) {
        mbar_wait(xfull + kb * 8, 0);
        load_afrags(&a[16 * kb], sb, kb, warp, lane);
        hmma(c0, &a[16 * kb], ONE2, ONE2); hmma(c1, &a[16 * kb + 4], ONE2, ONE2);
        hmma(c2, &a[16 * kb + 8], ONE2, ONE2); hmma(c3, &a[16 * kb + 12], ONE2, ONE2);
      }
      TS(0, 2);
      if (domod) {
        const float v = mod_finish(mw, reinterpret_cast<const bf16*>(smem + AUX_OFF + 1024), tid, reinterpret_cast<float*>(smem + AUX_OFF), 1);
        if (tid < 32) store_table(&g_tab1[(blockIdx.x % 36) * 4], v, blockIdx.x >= 36, 1.f, ~0u, lane);
      }
      float m0 = ((c0[0] + c1[0]) + (c2[0] + c3[0])) * (1.f / D_), m1 = ((c0[2] + c1[2]) + (c2[2] + c3[2])) * (1.f / D_);
      const uint32_t p0 = packbf(-m0, -m0), p1 = packbf(-m1, -m1);
      m0 += bflo(p0); m1 += bflo(p1);
#pragma unroll
      for (int i = 0; i < 4; i++) c0[i] = c1[i] = c2[i] = c3[i] = 0.f;
#pragma unroll
      for (int i = 0; i < 144; i += 4) {
        const uint32_t d0 = fma_bf2(a[i], ONE2, p0), d1 = fma_bf2(a[i + 1], ONE2, p1);
        const uint32_t d2 = fma_bf2(a[i + 2], ONE2, p0), d3 = fma_bf2(a[i + 3], ONE2, p1);
        hmma8(c0, d0, d1, d0); hmma8(c1, d0, d1, d1);
        hmma8(c2, d2, d3, d2); hmma8(c3, d2, d3, d3);
      }
      cen0 = __shfl_sync(0xffffffffu, p0, lane); cen1 = __shfl_sync(0xffffffffu, p1, lane);
      const bool odd = lane & 4;
      const int src = (lane & 28) | (lane >> 3);
      const float v0 = __shfl_sync(0xffffffffu, odd ? c0[1] + c2[1] : c0[0] + c2[0], src);
      const float v1 = __shfl_sync(0xffffffffu, odd ? c1[3] + c3[3] : c1[2] + c3[2], src);
      nrm = make_norm(m0, rsqrtf(fmaxf(fmaf(-m0, m0, v0 * (1.f / D_)), 0.f) + 1e-5f),
                      m1, rsqrtf(fmaxf(fmaf(-m1, m1, v1 * (1.f / D_)), 0.f) + 1e-5f));
    }
    TS(0, 3);
    if (lane < 4) mbar_arrive_cl(emptyc + (lane >> 1) * 8);
    named_bar(1, 256);
    if (tid < 144) {
      uint4 e;
#pragma unroll 1
      for (int it = 0; it < (1 << 20); it++) {
        asm volatile("ld.relaxed.gpu.global.v4.u32 {%0,%1,%2,%3}, [%4];" : "=r"(e.x), "=r"(e.y), "=r"(e.z), "=r"(e.w) : "l"(&g_tab1[tid]) : "memory");
        if (e.x && e.y && e.z && e.w) break;
        __nanosleep(40);
      }
      sts128(sb + AUX_OFF + tid * 16, ~e.x, ~e.y, ~e.z, ~e.w);
    }
    named_bar(1, 256);
    TS(0, 4);
    XRing r{2, 0u};
    const int row = warp * 16 + (lane >> 2), t = lane & 3;
    const int qper = 8 - j * 3;
    uint32_t off[9];
    {
      float acc[64];
      gemm_tile<false>(acc, a, sb + XR_OFF, fullb, emptyc, r, 0, 0, 0, lane,
                [&](int kb) {
                  center_afrags(&a[16 * kb], cen0, cen1);
                  modulate_afrags(&a[16 * kb], sb + AUX_OFF + t * 16, kb, nrm);
                }, NOP_HOOK);
      TS(0, 6);
      const int tt = t + (r.st - 4);
#pragma unroll
    for (int b = 0; b < 9; b++) {
      const int c = b * 8 + 2 * tt, slot = (c * 3641) >> 16, d = c - slot * 18;
      off[b] = sb + slot * 4608 + (d < 16 ? (d >> 3) * 2048 + row * 16 + (d & 7) * 2 : 4096 + row * 4);
    }
      qkv_stage_out<16, 0>(acc, off, t, qper);
      fence_async_smem();
      __syncwarp();
      if (lane == 0) mbar_arrive(ep1);
    }
    {
      float acc[44];
      gemm_tile<false>(acc, a, sb + XR_OFF, fullb, emptyc, r, 0, 0, 0, lane, NOP_HOOK, NOP_HOOK);
      TS(0, 7);
      qkv_stage_out<11, 16>(acc, off, t, qper);
    }
    fence_async_smem();
    named_bar(1, 256);
    const bool ship = lane < 2 && warp * 2 + lane < 15;
    if (ship) qkv_ship(sb, 21 + warp * 2 + lane, j, mb);
    TS(0, 8);
    if (ship) bulk_wait0_read();
    __syncwarp();
    cluster_sync();
    TS(0, 9);
  }
}

constexpr int PLANE = 32768;
constexpr int ATT_BAR = 6 * PLANE;
constexpr int SMEM_ATT = ATT_BAR + 2048 + 8192;
#define POLY_MASK 0xEEEE
__device__ __forceinline__ uint32_t exp2_pair(float y0, float y1) {
  const uint32_t pk = __byte_perm(__float_as_uint(y0), __float_as_uint(y1), 0x6521);
  const uint32_t z = pk & 0x007F007Fu;
  const uint32_t t = fma_h2(z, 0xF93FF93Fu, 0x35603560u);
  return pk + fma_h2(t, z, 0x837F8380u);
}
__device__ __forceinline__ void att_qk(float (&s)[64], const uint32_t (&q)[6], uint64_t dk, uint64_t dk2) {
  wg_fence();
  wgmma_rz_n128_t0(s, q[0], q[1], q[2], q[3], dk);
  wgmma_rs_n128_t0(s, q[4], q[5], 0u, 0u, dk2, 1);
  wg_commit();
  wg_wait<0>();
  fence_regs(s);
}
__device__ __forceinline__ void att_pv(float (&o)[12], uint32_t (&p)[32], uint64_t dv) {
  fence_regs(p);
  wg_fence();
#pragma unroll
  for (int k = 0; k < 8; k++) wgmma_rs_n24_t1(o, p[4 * k], p[4 * k + 1], p[4 * k + 2], p[4 * k + 3], dv + k * 16, 1);
  wg_commit();
  wg_wait<0>();
  fence_regs(o);
}

__device__ __forceinline__ bool wg_all(bool v, int warp) {
  int r;
  asm volatile("{\n.reg .pred p, r;\nsetp.ne.b32 p, %1, 0;\nbar.red.and.pred r, %2, 128, p;\nselp.b32 %0, 1, 0, r;\n}"
               : "=r"(r) : "r"((int)v), "r"(1 + (warp >> 2)) : "memory");
  return __all_sync(0xffffffffu, r);
}

__global__ void __launch_bounds__(512, 1)
attn_kernel(const bf16* __restrict__ cvec, const bf16* __restrict__ wmod, const bf16* __restrict__ wo,
            const bf16* __restrict__ wg, const bf16* __restrict__ wu, const bf16* __restrict__ wd) {
  extern __shared__ __align__(1024) uint8_t smem[];
  const uint32_t sb = smem_u32(smem);
  const int tid = threadIdx.x, lane = tid & 31, warp = tid >> 5;
  if (blockIdx.x < 4) {
    pdl_launch();
    TS(1, 0);
    const int b = blockIdx.x;
    if (tid == 0) {
      mbar_init(sb + ATT_BAR, 1);
      asm volatile("fence.mbarrier_init.release.cluster;" ::: "memory");
    }
    float acc[24];
#pragma unroll
    for (int e = 0; e < 24; e++) acc[e] = 0.f;
#pragma unroll 1
    for (int r = 0; r < 4; r++) {
      if (tid == 0) mbar_expect(sb + ATT_BAR, 144 * 1152);
      const float cv = __bfloat162float(cvec[r * 144 + warp * 9 + min(lane, 8)]);
      const float f = bfround(__fdividef(cv, 1.f + __expf(-cv)));
      __syncthreads();
      if (tid < 144) bulk_g2s(sb + tid * 1152, wmod + (size_t)(r * 144 + tid) * (6 * D_) + (2 + b) * D_, 1152, sb + ATT_BAR);
      mbar_wait(sb + ATT_BAR, r & 1);
#pragma unroll
      for (int i = 0; i < 9; i++) {
        const float fi = __shfl_sync(0xffffffffu, f, i);
#pragma unroll
        for (int c = 0; c < 3; c++) {
          const uint4 w = lds128(sb + (warp * 9 + i) * 1152 + min(c * 32 + lane, 71) * 16);
          acc[8 * c] += fi * bflo(w.x); acc[8 * c + 1] += fi * bfhi(w.x); acc[8 * c + 2] += fi * bflo(w.y); acc[8 * c + 3] += fi * bfhi(w.y);
          acc[8 * c + 4] += fi * bflo(w.z); acc[8 * c + 5] += fi * bfhi(w.z); acc[8 * c + 6] += fi * bflo(w.w); acc[8 * c + 7] += fi * bfhi(w.w);
        }
      }
    }
    __syncthreads();
    float* red = reinterpret_cast<float*>(smem);
#pragma unroll
    for (int e = 0; e < 24; e++)
      if (e < 16 || lane < 8) red[warp * D_ + ((e >> 3) * 32 + lane) * 8 + (e & 7)] = acc[e];
    __syncthreads();
#pragma unroll 1
    for (int u = warp; u < 36; u += 16) {
      float v = 0.f;
#pragma unroll
      for (int w = 0; w < 16; w++) v += red[w * D_ + u * 16 + (lane & 15)];
      v = bfround(v);
      if (b == 1 || b == 2) store_table(&g_tab2[u * 4], v, b == 2, 0.5f, 0u, lane);
      else if (lane < 16) g_mod[(2 + b) * D_ + u * 16 + lane] = v;
    }
    TS(1, 1);
    pdl_wait();
    if (blockIdx.x == 0 && tid < 144) g_tab1[tid] = make_uint4(0u, 0u, 0u, 0u);
    return;
  }
  const int head = (blockIdx.x - 4) >> 2, qc = (blockIdx.x - 4) & 3;
  const uint32_t bars = sb + ATT_BAR;
  if (tid == 0) {
    mbar_init(bars, 1);
    asm volatile("fence.mbarrier_init.release.cluster;" ::: "memory");
  }
  sts128(bars + 2048 + tid * 16, ~0u, ~0u, ~0u, ~0u);
  __syncthreads();
  pdl_launch();
  TS(1, 0);
  pdl_wait();
  TS(1, 1);
  const int g = lane >> 2, t = lane & 3;
  uint32_t qa[2][6];
  {
    uint4 k0[4], k1[4];
    uint32_t kx[4], vx[4];
#pragma unroll
    for (int i = 0; i < 4; i++) {
      k0[i] = __ldcg(&g_qkvp[(size_t)(32 + head) * 2 * S_ + i * 512 + tid]);
      k1[i] = __ldcg(&g_qkvp[(size_t)(32 + head) * 2 * S_ + S_ + i * 512 + tid]);
      kx[i] = __ldcg(&g_qkvx[(32 + head) * S_ + i * 512 + tid]);
      vx[i] = __ldcg(&g_qkvx[(64 + head) * S_ + i * 512 + tid]);
    }
    const uint32_t* qp = reinterpret_cast<const uint32_t*>(&g_qkvp[(size_t)head * 2 * S_]);
#pragma unroll
    for (int i = 0; i < 2; i++) {
      const int row = qc * 512 + i * 256 + warp * 16 + g;
      qa[i][0] = __ldcg(qp + row * 4 + t);
      qa[i][1] = __ldcg(qp + (row + 8) * 4 + t);
      qa[i][2] = __ldcg(qp + (S_ + row) * 4 + t);
      qa[i][3] = __ldcg(qp + (S_ + row + 8) * 4 + t);
      qa[i][4] = t == 0 ? __ldcg(&g_qkvx[head * S_ + row]) : 0u;
      qa[i][5] = t == 0 ? __ldcg(&g_qkvx[head * S_ + row + 8]) : 0u;
    }
    if (tid == 0) {
      mbar_expect(bars, 2 * PLANE);
      bulk_g2s(sb + 3 * PLANE, &g_qkvp[(size_t)(64 + head) * 2 * S_], 2 * PLANE, bars);
    }
    const bool pf = (POLY_MASK >> ((tid >> 3) & 15)) & 1;
    const uint32_t w1 = pf ? 0x3F803F80u : 0x00003F80u, w2 = pf ? 0x00003F80u : 0u;
    unsigned kb = 0;
#pragma unroll
    for (int i = 0; i < 4; i++) {
      const uint32_t d = sb + (i * 512 + tid) * 16;
      sts128(d, k0[i].x, k0[i].y, k0[i].z, k0[i].w);
      sts128(d + PLANE, k1[i].x, k1[i].y, k1[i].z, k1[i].w);
      sts128(d + 2 * PLANE, kx[i], w1, w2, 0);
      sts128(d + 5 * PLANE, vx[i], 0x3F80u, 0, 0);
      uint32_t n = fma_bf2(kx[i], kx[i], 0u);
      n = fma_bf2(k0[i].x, k0[i].x, n); n = fma_bf2(k0[i].y, k0[i].y, n); n = fma_bf2(k0[i].z, k0[i].z, n); n = fma_bf2(k0[i].w, k0[i].w, n);
      n = fma_bf2(k1[i].x, k1[i].x, n); n = fma_bf2(k1[i].y, k1[i].y, n); n = fma_bf2(k1[i].z, k1[i].z, n); n = fma_bf2(k1[i].w, k1[i].w, n);
      kb = max(kb, __float_as_uint(bflo(n) + bfhi(n)));
    }
    kb = __reduce_max_sync(0xffffffffu, kb);
    if (lane == 0) sts32(bars + 64 + warp * 4, kb);
  }
  fence_async_smem();
  __syncthreads();
  TS(1, 2);
  TC(1, 14);
  const float kmax = sqrtf(__uint_as_float(__reduce_max_sync(0xffffffffu, lds32(bars + 64 + (lane & 15) * 4))) + 1e-30f) * 1.04f;
  if (warp == 14 && lane < 12) {
    const int c = blockIdx.x - 4;
    if (lane < 8) bulk_s2g(&g_last[c * 4096 + lane * 512], bars + 2048, 8192);
    else if (lane < 11) bulk_s2g(g_x1 + (c * 3 + lane - 8) * 3072, bars + 2048, 6144);
    else bulk_s2g(&g_stat[c * 128], bars + 2048, 1024);
    bulk_commit();
  }
  if (warp == 15) {
    const int c = blockIdx.x - 4;
    const bf16* w = lane < 8 ? wg : lane < 16 ? wu : wd;
    if (lane < 24) l2_prefetch(reinterpret_cast<const char*>(w) + (c * 8 + (lane & 7)) * 5184, 5184);
    else if (lane == 24) l2_prefetch(reinterpret_cast<const char*>(wo) + c * 5184, 5184);
  }
  const uint64_t dk0 = mkdesc(sb, PLANE, 128, 0), dk2 = mkdesc(sb + 2 * PLANE, 3 * PLANE, 128, 0), dv0 = mkdesc(sb + 3 * PLANE, 128, PLANE, 0);
#pragma unroll 1
  for (int qt = 0; qt < 2; qt++) {
    uint32_t q[6];
#pragma unroll
    for (int i = 0; i < 6; i++) q[i] = qt ? qa[1][i] : qa[0][i];
    float n0 = 0.f, n1 = 0.f;
#pragma unroll
    for (int i = 0; i < 3; i++) {
      n0 = fmaf(bflo(q[2 * i]), bflo(q[2 * i]), n0); n0 = fmaf(bfhi(q[2 * i]), bfhi(q[2 * i]), n0);
      n1 = fmaf(bflo(q[2 * i + 1]), bflo(q[2 * i + 1]), n1); n1 = fmaf(bfhi(q[2 * i + 1]), bfhi(q[2 * i + 1]), n1);
    }
    n0 += __shfl_xor_sync(0xffffffffu, n0, 1); n0 += __shfl_xor_sync(0xffffffffu, n0, 2);
    n1 += __shfl_xor_sync(0xffffffffu, n1, 1); n1 += __shfl_xor_sync(0xffffffffu, n1, 2);
    const float b0 = sqrtf(n0) * kmax, b1 = sqrtf(n1) * kmax;
    bool safe = wg_all(b0 <= 87.f && b1 <= 87.f, warp);
    float o[12];
#pragma unroll
    for (int i = 0; i < 12; i++) o[i] = 0.f;
    if (safe) {
      if (t == 1) { q[4] = packbf(b0 * (-1.f / 3.f), 376.f); q[5] = packbf(b1 * (-1.f / 3.f), 376.f); }
      if (t == 2) { q[4] = q[5] = 0x3BB0u; }
#pragma unroll 1
      for (int kb = 0; kb < 16; kb++) {
        float s[64];
        att_qk(s, q, dk0 + kb * 128, dk2 + kb * 128);
        uint32_t p[32];
#pragma unroll
        for (int b = 0; b < 16; b++) {
          if ((POLY_MASK >> b) & 1) {
            p[2 * b] = exp2_pair(s[4 * b], s[4 * b + 1]);
            p[2 * b + 1] = exp2_pair(s[4 * b + 2], s[4 * b + 3]);
          } else {
            p[2 * b] = packbf(ex2f(s[4 * b]), ex2f(s[4 * b + 1]));
            p[2 * b + 1] = packbf(ex2f(s[4 * b + 2]), ex2f(s[4 * b + 3]));
          }
        }
        if ((qt | kb) == 0) mbar_wait(bars, 0);
        att_pv(o, p, dv0 + kb * 128);
      }
      float mx = 0.f;
#pragma unroll
      for (int i = 0; i < 12; i++) mx = fmaxf(mx, fabsf(o[i]) <= 3e38f ? 0.f : 1.f);
      safe = wg_all(mx == 0.f && (t != 1 || (o[8] >= 1e-18f && o[10] >= 1e-18f)), warp);
    }
    if (!safe) {
      if (t != 0) q[4] = q[5] = 0u;
#pragma unroll
      for (int i = 0; i < 12; i++) o[i] = 0.f;
      mbar_wait(bars, 0);
      float x0 = -INFINITY, x1 = -INFINITY;
#pragma unroll 1
      for (int kb = 0; kb < 16; kb++) {
        float s[64];
        att_qk(s, q, dk0 + kb * 128, dk2 + kb * 128);
#pragma unroll
        for (int b = 0; b < 16; b++) { x0 = fmaxf(x0, fmaxf(s[4 * b], s[4 * b + 1])); x1 = fmaxf(x1, fmaxf(s[4 * b + 2], s[4 * b + 3])); }
      }
      x0 = fmaxf(x0, __shfl_xor_sync(0xffffffffu, x0, 1)); x0 = fmaxf(x0, __shfl_xor_sync(0xffffffffu, x0, 2));
      x1 = fmaxf(x1, __shfl_xor_sync(0xffffffffu, x1, 1)); x1 = fmaxf(x1, __shfl_xor_sync(0xffffffffu, x1, 2));
#pragma unroll 1
      for (int kb = 0; kb < 16; kb++) {
        float s[64];
        att_qk(s, q, dk0 + kb * 128, dk2 + kb * 128);
        uint32_t p[32];
#pragma unroll
        for (int b = 0; b < 16; b++) {
          p[2 * b] = packbf(ex2f(s[4 * b] - x0), ex2f(s[4 * b + 1] - x0));
          p[2 * b + 1] = packbf(ex2f(s[4 * b + 2] - x1), ex2f(s[4 * b + 3] - x1));
        }
        att_pv(o, p, dv0 + kb * 128);
      }
    }
    TS(1, 3 + qt * 2 + !safe);
    TC(1, 15);
    const float l0 = 1.f / __shfl_sync(0xffffffffu, o[8], (lane & 28) | 1), l1 = 1.f / __shfl_sync(0xffffffffu, o[10], (lane & 28) | 1);
    const int row = qc * 512 + qt * 256 + warp * 16 + g;
    uint32_t* op = reinterpret_cast<uint32_t*>(g_o + (size_t)row * D_ + head * 18) + t;
    op[0] = packbf(o[0] * l0, o[1] * l0);
    op[4] = packbf(o[4] * l0, o[5] * l0);
    op[4 * D_] = packbf(o[2] * l1, o[3] * l1);
    op[4 * D_ + 4] = packbf(o[6] * l1, o[7] * l1);
    if (t == 0) { op[8] = packbf(o[8] * l0, o[9] * l0); op[4 * D_ + 8] = packbf(o[10] * l1, o[11] * l1); }
  }
  bulk_wait0();
}

__device__ __forceinline__ void acq_fence() { asm volatile("fence.proxy.async.global;" ::: "memory"); }
#define WTL 3
__device__ __forceinline__ float2 ld_rlx2(const float2* p) {
  float2 v;
  asm volatile("ld.relaxed.gpu.global.v2.f32 {%0,%1}, [%2];" : "=f"(v.x), "=f"(v.y) : "l"(p) : "memory");
  return v;
}
__device__ __forceinline__ void load_valid_afrags(uint32_t* a, uint32_t sb, int kb, int warp, int lane, const bf16* rows, uint32_t sw) {
#pragma unroll 1
  for (int it = 0; it < (1 << 20); it++) {
    load_afrags(a, sb, kb, warp, lane);
    uint32_t mx = 0;
#pragma unroll
    for (int i = 0; i < 16; i++) mx = max(mx, a[i]);
    if (__all_sync(0xffffffffu, mx != ~0u)) break;
#pragma unroll
    for (int i = 0; i < 4; i++) {
      uint4 v;
      asm volatile("ld.relaxed.gpu.global.v4.u32 {%0,%1,%2,%3}, [%4];" : "=r"(v.x), "=r"(v.y), "=r"(v.z), "=r"(v.w) : "l"(rows + kb * 64 + i * 8) : "memory");
      sts128(kb * 16384 + (sw ^ (i << 4)), v.x, v.y, v.z, v.w);
    }
    fence_async_smem();
    __syncwarp();
  }
}
#define mbar_wait mbar_wait_c
#define LO0(t) ((t) < 2 ? 2 : (t) >= 7 && (t) < 10)
#define LO1(t) ((t) < 1 ? 2 : (t) >= 7 && (t) < 9)
__global__ void __launch_bounds__(384, 1)
ffn_kernel(const __grid_constant__ CUtensorMap tm_o, const __grid_constant__ CUtensorMap tm_wo,
           const __grid_constant__ CUtensorMap tm_x1, const __grid_constant__ CUtensorMap tm_g,
           const __grid_constant__ CUtensorMap tm_u, const __grid_constant__ CUtensorMap tm_d,
           const __grid_constant__ CUtensorMap tm_out, const bf16* __restrict__ x, bf16* __restrict__ out) {
  extern __shared__ __align__(1024) uint8_t smem[];
  const uint32_t sb = smem_u32(smem);
  const uint32_t fullb = sb + BAR_OFF, emptyb = fullb + 64, inbox = fullb + 56, stfree = fullb + 120, wrote = fullb + 128,
                 xfull = fullb + 160;
  const int tid = threadIdx.x, lane = tid & 31, warp = tid >> 5;
  const int mb = blockIdx.x & 15, j = blockIdx.x >> 4;
  if (tid == 0) {
    for (int i = 0; i < 7; i++) { mbar_init(fullb + i * 8, 1); mbar_init(emptyb + i * 8, 16); }
    for (int i = 0; i < 9; i++) mbar_init(xfull + i * 8, 1);
    mbar_init(inbox, 7); mbar_init(stfree, 1);
    for (int i = 0; i < 3; i++) mbar_init(wrote + i * 8, 8);
    asm volatile("fence.mbarrier_init.release.cluster;" ::: "memory");
  }
  __syncwarp();
  cluster_sync();
  if (warp >= 8) {
    reg_dealloc<24>();
    if (warp == 8) {
      if (lane == (mb & 1)) {
        XRing r{2, 0x7Cu};
        auto load = [&](const CUtensorMap* tm, int c0, int c1, bool both, bool d3 = false) {
          mbar_wait(emptyb + r.st * 8, (r.ph >> r.st) & 1);
          const uint32_t dst = sb + XR_OFF + r.st * 16384 + lane * 8192, bar = fullb + r.st * 8;
          mbar_expect(bar, both ? 16384 : 8192);
          if (d3) tma3d_mc(dst, tm, c0, j, c1, bar);
          else if (both || lane == 0) tma2d_mc(dst, tm, c0, c1, bar);
        };
#pragma unroll 1
        for (int kb = 0; kb < 9; kb++) { load(&tm_wo, lane * 64, kb * 64, true, true); xr_next(r, 2); }
        mbar_wait(xfull + 64, 0);
#pragma unroll 1
        for (int nt = 0; nt < 9; nt++)
#pragma unroll 1
          for (int kb = 0; kb < 9; kb++) {
            load(lane ? &tm_u : &tm_g, j * 576 + nt * 64, kb * 64, true);
            xr_next(r, kb < 4 ? LO0(nt) : kb < 8 ? LO1(nt) : LO0(nt + 1));
          }
        mbar_wait(emptyb, r.ph & 1);
        r.ph ^= 1u;
#pragma unroll 1
        for (int sl = 0; sl < 4; sl++) {
          const int c0 = (sl | lane) == 0 ? 512 : ((j + 2 * sl + lane) & 7) * 64;
#pragma unroll 1
          for (int kb = 0; kb < 9; kb++) {
            load(&tm_d, c0, j * 576 + kb * 64, true);
            xr_next(r, sl == 0 && kb < 4);
          }
        }
#pragma unroll 1
        for (int i = 0; i < 5; i++) {
          load(&tm_d, j * 64, j * 576 + (2 * i + lane) * 64, i < 4);
          xr_next(r, 0);
        }
      }
    } else if (warp == 9) {
      if (lane == 0) {
        prefetch_tmap(&tm_o); prefetch_tmap(&tm_x1); prefetch_tmap(&tm_d); prefetch_tmap(&tm_out);
        pdl_wait();
#pragma unroll 1
        for (int kb = 0; kb < 9; kb++) {
          mbar_expect(xfull + kb * 8, kb < 8 ? 16384 : 16384 + 2304);
          tma2d(sb + kb * 16384, &tm_o, kb * 64, mb * 128, xfull + kb * 8);
          tma2d(sb + kb * 16384 + 8192, &tm_o, kb * 64, mb * 128 + 64, xfull + kb * 8);
        }
        bulk_g2s(sb + AUX_OFF, g_tab2, 2304, xfull + 64);
        mbar_wait(stfree, 0);
        acq_fence();
#pragma unroll 1
        for (int kb = 0; kb < 9; kb++) {
          mbar_expect(xfull + kb * 8, 16384);
          tma2d(sb + kb * 16384, &tm_x1, kb * 64, mb * 128, xfull + kb * 8);
          tma2d(sb + kb * 16384 + 8192, &tm_x1, kb * 64, mb * 128 + 64, xfull + kb * 8);
        }
#pragma unroll 1
        for (int sl = 0; sl < 3; sl++) {
          mbar_wait(wrote + sl * 8, 0);
          if (sl == 0) {
#pragma unroll 1
            for (int w = 0; w < 8; w++) bulk_s2g(&g_part8[((mb * 8 + w) * 8 + j) * 128], sb + w * 2048, 2048);
          } else {
            bulk_s2g(sl == 1 ? &g_part[((mb * 8 + ((j + 2) & 7)) * 8 + j) * 1024] : &g_last[(mb * 8 + ((j + 4) & 7)) * 4096], sb, 16384);
          }
          bulk_s2g(sl < 2 ? &g_part[((mb * 8 + ((j + 2 * sl + 1) & 7)) * 8 + j) * 1024] : &g_last[(mb * 8 + ((j + 5) & 7)) * 4096 + 1024], sb + 16384, 16384);
          bulk_commit();
          bulk_wait0_read();
          mbar_arrive(stfree);
          TX(0, 6 + sl);
          bulk_wait0();
          if (sl < 2) {
            asm volatile("fence.proxy.async.global;" ::: "memory");
            asm volatile("fence.acq_rel.gpu;" ::: "memory");
          }
          asm volatile("st.relaxed.gpu.global.u32 [%0], %1;" ::"l"(&g_flag_p8[(mb * 8 + j) * 32]), "r"(sl + 1) : "memory");
          TX(1, 6 + sl);
        }
      }
    } else if (warp == 10) {
      const int src = (j - lane) & 7;
#pragma unroll 1
      for (int sl = 0; sl < 3; sl++) {
        mbar_wait(wrote + sl * 8, 0);
        if (sl == 2) mbar_wait(stfree, 1);
        if (lane > 0 && (lane >> 1) == sl) {
          spin_ge(&g_flag_p8[(mb * 8 + src) * 32], sl + 1);
          acq_fence();
          TX(lane & 1, 10 + sl);
          mbar_expect(inbox, 16384);
          if (sl < 2) bulk_g2s(sb + (lane + 1) * 16384, &g_part[((mb * 8 + j) * 8 + src) * 1024], 16384, inbox);
          else bulk_g2s(sb + (lane - 4) * 16384, &g_last[((mb * 8 + j) * 4 + lane - 4) * 1024], 16384, inbox);
        }
        __syncwarp();
      }
    } else {
      mbar_wait(wrote, 0);
      if (lane < 8) spin_ge(&g_flag_p8[(mb * 8 + lane) * 32], 1);
      __syncwarp();
      acq_fence();
      if (lane == 0) mbar_expect(inbox, 2048 + 512);
      __syncwarp();
      if (lane < 16) bulk_g2s(sb + AUX_OFF + lane * 128, g_x1 + (size_t)(mb * 128 + j * 16 + lane) * D_ + 512, 128, inbox);
      else if (lane < 18) bulk_g2s(sb + GB_OFF + (lane - 16) * 256, g_mod + 5 * D_ + (lane == 16 ? j * 64 : 512), 256, inbox);
      if (lane == 0) {
        mbar_expect(inbox, 32768);
        bulk_g2s(sb + 5 * 16384, &g_part8[(mb * 8 + j) * 8 * 128], 16384, inbox);
        tma2d(sb + 6 * 16384, &tm_x1, j * 64, mb * 128, inbox);
        tma2d(sb + 6 * 16384 + 8192, &tm_x1, j * 64, mb * 128 + 64, inbox);
      }
    }
  } else {
    reg_alloc<240>();
    const int t = lane & 3;
    const int row = mb * 128 + warp * 16 + (lane >> 2);
    XRing r{2, 0u};
    const uint32_t emptyc = mapa(emptyb, lane & 1);
    {
      const int col = j * 72 + 2 * t;
      uint32_t xr[18];
#pragma unroll
      for (int b = 0; b < 9; b++) {
        xr[2 * b] = __ldg(reinterpret_cast<const uint32_t*>(x + (size_t)row * D_ + col + b * 8));
        xr[2 * b + 1] = __ldg(reinterpret_cast<const uint32_t*>(x + (size_t)(row + 8) * D_ + col + b * 8));
      }
      TS(2, 0);
      pdl_wait();
      TS(2, 1);
      float2 ga[9];
#pragma unroll
      for (int b = 0; b < 9; b++) ga[b] = __ldcg(reinterpret_cast<const float2*>(g_mod + 2 * D_ + col + b * 8));
      float acc[36];
      int prev = 0;
#pragma unroll
      for (int i = 0; i < 36; i++) acc[i] = 0.f;
#pragma unroll 1
      for (int kb = 0; kb < 9; kb++) {
        mbar_wait(fullb + r.st * 8, (r.ph >> r.st) & 1);
        mbar_wait(xfull + kb * 8, 0);
        if (kb == 0) TS(2, 2);
        if (kb == 8) TS(2, 3);
        const uint64_t da = mkdesc(sb + kb * 16384 + (warp >> 2) * 8192, 16, 1024, 1);
        const uint64_t db = mkdesc(sb + XR_OFF + r.st * 16384, 8192, 1024, 1);
        wg_fence();
#pragma unroll
        for (int ks = 0; ks < 4; ks++) wgmma_ss_n72_t1(acc, da + ks * 2, db + ks * 128, true);
        wg_commit();
        wg_wait<1>();
        if (kb > 0 && lane < 2) mbar_arrive_cl(emptyc + prev * 8);
        prev = r.st;
        xr_next(r, 2);
      }
      wg_wait<0>();
      if (lane < 2) mbar_arrive_cl(emptyc + prev * 8);
      fence_regs(acc);
      TS(2, 4);
      const uint32_t sg = sb + warp * 2048;
      float s0 = 0.f, s1 = 0.f;
#pragma unroll
      for (int b = 0; b < 9; b++) {
        xr[2 * b] = packbf(fmaf(ga[b].x, acc[4 * b], bflo(xr[2 * b])), fmaf(ga[b].y, acc[4 * b + 1], bfhi(xr[2 * b])));
        xr[2 * b + 1] = packbf(fmaf(ga[b].x, acc[4 * b + 2], bflo(xr[2 * b + 1])), fmaf(ga[b].y, acc[4 * b + 3], bfhi(xr[2 * b + 1])));
        sts32(sg + (lane >> 2) * 144 + b * 16 + t * 4, xr[2 * b]);
        sts32(sg + 16384 + (lane >> 2) * 144 + b * 16 + t * 4, xr[2 * b + 1]);
        s0 += bflo(xr[2 * b]) + bfhi(xr[2 * b]);
        s1 += bflo(xr[2 * b + 1]) + bfhi(xr[2 * b + 1]);
      }
      __syncwarp();
#pragma unroll
      for (int i = 0; i < 5; i++) {
        const int c = i * 32 + lane, rr = c / 9;
        if (c < 144) __stcg(reinterpret_cast<uint4*>(g_x1 + (size_t)(mb * 128 + warp * 16 + rr) * D_ + j * 72) + (c - rr * 9), lds128(sg + (rr >> 3) * (16384 - 1152) + c * 16));
      }
      s0 += __shfl_xor_sync(0xffffffffu, s0, 1); s0 += __shfl_xor_sync(0xffffffffu, s0, 2);
      s1 += __shfl_xor_sync(0xffffffffu, s1, 1); s1 += __shfl_xor_sync(0xffffffffu, s1, 2);
      s0 *= (1.f / 72.f); s1 *= (1.f / 72.f);
      float v0 = 0.f, v1 = 0.f;
#pragma unroll
      for (int b = 0; b < 9; b++) {
        const float e0 = bflo(xr[2 * b]) - s0, e1 = bfhi(xr[2 * b]) - s0, e2 = bflo(xr[2 * b + 1]) - s1, e3 = bfhi(xr[2 * b + 1]) - s1;
        v0 = fmaf(e0, e0, v0); v0 = fmaf(e1, e1, v0); v1 = fmaf(e2, e2, v1); v1 = fmaf(e3, e3, v1);
      }
      v0 += __shfl_xor_sync(0xffffffffu, v0, 1); v0 += __shfl_xor_sync(0xffffffffu, v0, 2);
      v1 += __shfl_xor_sync(0xffffffffu, v1, 1); v1 += __shfl_xor_sync(0xffffffffu, v1, 2);
      __stcg(reinterpret_cast<float*>(&g_stat[(mb * 8 + j) * 128 + warp * 16 + (lane >> 2) + (t >> 1) * 8]) + (t & 1), t == 0 ? s0 : t == 1 ? v0 : t == 2 ? s1 : v1);
      __syncwarp();
      if (lane == 0) asm volatile("red.relaxed.gpu.global.add.u32 [%0], 1;" ::"l"(&g_flag_x1[mb * 32]) : "memory");
      TS(2, 5);
      if (lane == 0) spin_ge(&g_flag_x1[mb * 32], 64);
      __syncwarp();
    }
    TS(3, 1);
    float m0, r0, m1, r1;
    {
      const float2* sp = &g_stat[(mb * 8 + 2 * t) * 128 + warp * 16 + (lane >> 2)];
      if (tid == 0) mbar_arrive(stfree);
      float2 a0, a1, c0, c1;
#pragma unroll 1
      for (int it = 0; it < (1 << 20); it++) {
        a0 = ld_rlx2(sp); a1 = ld_rlx2(sp + 128); c0 = ld_rlx2(sp + 8); c1 = ld_rlx2(sp + 136);
        const uint32_t mx = max(max(max(__float_as_uint(a0.x), __float_as_uint(a0.y)), max(__float_as_uint(a1.x), __float_as_uint(a1.y))),
                                max(max(__float_as_uint(c0.x), __float_as_uint(c0.y)), max(__float_as_uint(c1.x), __float_as_uint(c1.y))));
        if (__all_sync(0xffffffffu, mx != ~0u)) break;
      }
      const float4 sa = make_float4(a0.x, a0.y, a1.x, a1.y), sc = make_float4(c0.x, c0.y, c1.x, c1.y);
      m0 = sa.x + sa.z; m1 = sc.x + sc.z;
      m0 += __shfl_xor_sync(0xffffffffu, m0, 1); m0 += __shfl_xor_sync(0xffffffffu, m0, 2);
      m1 += __shfl_xor_sync(0xffffffffu, m1, 1); m1 += __shfl_xor_sync(0xffffffffu, m1, 2);
      m0 *= 0.125f; m1 *= 0.125f;
      float v0 = sa.y + sa.w + 72.f * ((sa.x - m0) * (sa.x - m0) + (sa.z - m0) * (sa.z - m0));
      float v1 = sc.y + sc.w + 72.f * ((sc.x - m1) * (sc.x - m1) + (sc.z - m1) * (sc.z - m1));
      v0 += __shfl_xor_sync(0xffffffffu, v0, 1); v0 += __shfl_xor_sync(0xffffffffu, v0, 2);
      v1 += __shfl_xor_sync(0xffffffffu, v1, 1); v1 += __shfl_xor_sync(0xffffffffu, v1, 2);
      r0 = rsqrtf(v0 * (1.f / D_) + 1e-5f); r1 = rsqrtf(v1 * (1.f / D_) + 1e-5f);
    }
    const uint32_t p0 = packbf(-m0, -m0), p1 = packbf(-m1, -m1);
    const Norm nrm = make_norm(m0 + bflo(p0), r0, m1 + bflo(p1), r1);
    uint32_t a[144];
    TS(3, 3);
    TC(3, 14);
    const uint32_t stash = sb + warp * 2048 + lane * 16;
    {
    float acc[64];
    {
      gemm_tile<false>(acc, a, sb + XR_OFF, fullb, emptyc, r, 2, 2, 2, lane,
                [&](int kb) {
                  mbar_wait(xfull + kb * 8, 1);
                  load_valid_afrags(&a[16 * kb], sb, kb, warp, lane, g_x1 + (mb * 128 + (tid >> 1)) * D_ + (lane & 1) * 32,
                                    (sb + tid * 64) ^ ((lane & 14) << 3));
                  center_afrags(&a[16 * kb], p0, p1);
                  modulate_afrags(&a[16 * kb], sb + AUX_OFF + t * 16, kb, nrm);
                }, [&](int kb) { if (kb == 8 && lane < 4) mbar_arrive_cl(emptyc + (lane >> 1) * 8); });
      TS(3, 4);
    }
#pragma unroll 1
    for (int nt = 0;;) {
      if (nt == 4) TS(3, 5);
      if (nt < 9) {
        uint32_t p[16];
#pragma unroll
        for (int i = 0; i < 16; i++)
          p[i] = packbf(fmaf(tanhf_(acc[2 * i]), acc[32 + 2 * i], acc[32 + 2 * i]), fmaf(tanhf_(acc[2 * i + 1]), acc[33 + 2 * i], acc[33 + 2 * i]));
        if (nt < 8) {
#pragma unroll
          for (int ks = 0; ks < 4; ks++) sts128(stash + nt * 16384 + ks * 512, p[4 * ks], p[4 * ks + 1], p[4 * ks + 2], p[4 * ks + 3]);
        } else {
#pragma unroll
          for (int n = 0; n < 32; n++) {
            const int i = (n + 28) % 32;
            const uint4 v = lds128(stash + (i >> 2) * 16384 + (i & 3) * 512);
            a[4 * i] = v.x; a[4 * i + 1] = v.y; a[4 * i + 2] = v.z; a[4 * i + 3] = v.w;
          }
#pragma unroll
          for (int i = 0; i < 16; i++) a[128 + i] = p[i];
          fence_regs(a);
          TS(3, 6);
          TC(3, 15);
        }
      } else {
      const int sl = nt - 9;
      if (sl == 3) {
#pragma unroll
        for (int i = 0; i < 8; i++)
          __stcg(&g_last[((mb * 8 + ((j + 6 + (i >> 2)) & 7)) * 4 + 2 + (i >> 2)) * 1024 + warp * 128 + (i & 3) * 32 + lane],
                 make_uint4(packbf(acc[8 * i], acc[8 * i + 1]), packbf(acc[8 * i + 2], acc[8 * i + 3]),
                            packbf(acc[8 * i + 4], acc[8 * i + 5]), packbf(acc[8 * i + 6], acc[8 * i + 7])));
        TS(3, 10);
        break;
      }
      if (sl > 0) mbar_wait(stfree, sl & 1);
#pragma unroll
      for (int i = 0; i < 8; i++)
        sts128(stash + (i >> 2) * 16384 + (i & 3) * 512, packbf(acc[8 * i], acc[8 * i + 1]), packbf(acc[8 * i + 2], acc[8 * i + 3]),
               packbf(acc[8 * i + 4], acc[8 * i + 5]), packbf(acc[8 * i + 6], acc[8 * i + 7]));
      fence_async_smem();
      TS(3, 7 + sl);
      __syncwarp();
      if (lane == 0) mbar_arrive(wrote + sl * 8);
      }
      nt++;
      if ((nt & 3) == 1 && warp >= 4) named_bar(2, 256);
      gemm_tile<false>(acc, a, sb + XR_OFF, fullb, emptyc, r, LO0(nt), LO1(nt), LO0(nt + 1), lane, NOP_HOOK,
                [&](int kb) {
                  if (kb == 0 && nt == 9 && lane < 2) mbar_arrive_cl(emptyc);
                  if (kb == 1 && (nt & 3) == 1 && warp < 4) named_arrive(2, 256);
                });
    }
    }
    float acc[32];
    const int o8 = (mb * 128 + j * 16 + (lane >> 2)) * D_ + 512 + warp * 8 + 2 * t;
    asm volatile("barrier.cluster.arrive.relaxed;" ::: "memory");
#pragma unroll
    for (int i = 0; i < 5; i++) {
      mbar_wait(fullb + r.st * 8, (r.ph >> r.st) & 1);
      const uint64_t db = mkdesc(sb + XR_OFF + r.st * 16384, 8192, 1024, 1);
      wg_fence();
#pragma unroll
      for (int ks = 0; ks < (i < 4 ? 8 : 4); ks++) mma_rs(acc, &a[32 * i + 4 * ks], db + ks * 128, (i | ks) != 0);
      wg_commit();
      xr_next(r, 0);
    }
    float ps[32];
    auto add_in = [&](float (&d)[32], int l, bool first) {
#pragma unroll
      for (int i = 0; i < 4; i++) {
        const uint4 v = lds128(stash + l * 16384 + i * 512);
        const uint32_t u[4] = {v.x, v.y, v.z, v.w};
#pragma unroll
        for (int e = 0; e < 4; e++) {
          d[8 * i + 2 * e] = first ? bflo(u[e]) : d[8 * i + 2 * e] + bflo(u[e]);
          d[8 * i + 2 * e + 1] = first ? bfhi(u[e]) : d[8 * i + 2 * e + 1] + bfhi(u[e]);
        }
      }
    };
    wg_wait<WTL>();
    {
      const uint4* lp = &g_last[(mb * 8 + j) * 4096 + warp * 128 + lane];
      uint32_t u[32], v[32];
      auto fetch = [&](uint32_t (&d)[32], int o) {
#pragma unroll
        for (int i = 0; i < 8; i++)
          asm volatile("ld.relaxed.gpu.global.v4.u32 {%0,%1,%2,%3}, [%4];" : "=r"(d[4 * i]), "=r"(d[4 * i + 1]), "=r"(d[4 * i + 2]), "=r"(d[4 * i + 3])
                       : "l"(lp + o + (i >> 2) * 1024 + (i & 3) * 32) : "memory");
      };
      auto settle = [&](uint32_t (&d)[32], int o) {
#pragma unroll 1
        for (int it = 0; it < (1 << 20); it++) {
          uint32_t mx = 0;
#pragma unroll
          for (int i = 0; i < 32; i++) mx = max(mx, d[i]);
          if (__all_sync(0xffffffffu, mx != ~0u)) break;
          fetch(d, o);
        }
#pragma unroll
        for (int i = 0; i < 16; i++) { ps[2 * i] += bflo(d[i]) + bflo(d[16 + i]); ps[2 * i + 1] += bfhi(d[i]) + bfhi(d[16 + i]); }
      };
      fetch(u, 2048);
      mbar_wait(inbox, 0);
#pragma unroll
      for (int i = 0; i < 32; i++) ps[i] = 0.f;
#pragma unroll 1
      for (int l = 2; l < 5; l++) add_in(ps, l, false);
#pragma unroll
      for (int i = 0; i < 8; i++) {
        const uint4 w = lds128(stash + (i >> 2) * 16384 + (i & 3) * 512);
        v[4 * i] = w.x; v[4 * i + 1] = w.y; v[4 * i + 2] = w.z; v[4 * i + 3] = w.w;
      }
#pragma unroll 1
      for (int h = 0; h < 2; h++) {
        settle(v, h * 2048);
#pragma unroll
        for (int i = 0; i < 32; i++) v[i] = u[i];
      }
    }
    fence_regs(ps);
    TS(3, 12);
    wg_wait<0>();
    fence_regs(acc);
#pragma unroll
    for (int i = 0; i < 32; i++) acc[i] += ps[i];
    uint32_t xr[16];
    load_afrags(xr, sb, 6, warp, lane);
#pragma unroll
    for (int b = 0; b < 8; b++) {
      const float gx = __uint_as_float(lds32(sb + GB_OFF + b * 32 + t * 8)), gy = __uint_as_float(lds32(sb + GB_OFF + b * 32 + t * 8 + 4));
      xr[2 * b] = packbf(fmaf(gx, acc[4 * b], bflo(xr[2 * b])), fmaf(gy, acc[4 * b + 1], bfhi(xr[2 * b])));
      xr[2 * b + 1] = packbf(fmaf(gx, acc[4 * b + 2], bflo(xr[2 * b + 1])), fmaf(gy, acc[4 * b + 3], bfhi(xr[2 * b + 1])));
    }
    __syncwarp();
    const uint32_t ob = sb + 2 * 16384 + warp * 2048;
#pragma unroll
    for (int i = 0; i < 4; i++)
      stsm4(ob + (lane & 15) * 128 + (((2 * i + (lane >> 4)) ^ (lane & 7)) << 4), xr[4 * i], xr[4 * i + 1], xr[4 * i + 2], xr[4 * i + 3]);
    fence_async_smem();
    __syncwarp();
    if (lane == 0) {
      tma_store2d(&tm_out, j * 64, mb * 128 + warp * 16, ob);
      bulk_commit();
    }
    {
      float e0 = 0.f, e1 = 0.f, e2 = 0.f, e3 = 0.f;
#pragma unroll 2
      for (int s = 0; s < 8; s++) {
        const uint32_t p8 = sb + 5 * 16384 + s * 2048 + (warp >> 1) * 512 + lane * 16 + (warp & 1) * 8;
        const uint32_t u0 = lds32(p8), u1 = lds32(p8 + 4);
        e0 += bflo(u0); e1 += bfhi(u0); e2 += bflo(u1); e3 += bfhi(u1);
      }
      const uint32_t x80 = lds32(sb + AUX_OFF + (lane >> 2) * 128 + warp * 16 + t * 4), x81 = lds32(sb + AUX_OFF + 1024 + (lane >> 2) * 128 + warp * 16 + t * 4);
      const float2 gb8 = make_float2(__uint_as_float(lds32(sb + GB_OFF + 256 + warp * 32 + t * 8)), __uint_as_float(lds32(sb + GB_OFF + 260 + warp * 32 + t * 8)));
      *reinterpret_cast<uint32_t*>(out + o8) = packbf(fmaf(gb8.x, e0, bflo(x80)), fmaf(gb8.y, e1, bfhi(x80)));
      *reinterpret_cast<uint32_t*>(out + o8 + 8 * D_) = packbf(fmaf(gb8.x, e2, bflo(x81)), fmaf(gb8.y, e3, bfhi(x81)));
    }
    if (lane == 0) bulk_wait0_read();
    __syncwarp();
    asm volatile("barrier.cluster.wait;" ::: "memory");
    TS(3, 13);
  }
}

typedef CUresult (*EncodeFn)(CUtensorMap*, CUtensorMapDataType, cuuint32_t, void*, const cuuint64_t*, const cuuint64_t*,
                             const cuuint32_t*, const cuuint32_t*, CUtensorMapInterleave, CUtensorMapSwizzle,
                             CUtensorMapL2promotion, CUtensorMapFloatOOBfill);
static void make_map(EncodeFn enc, CUtensorMap* m, const void* p, int rows, int cols, int boxrows, int boxcols = 64) {
  cuuint64_t gd[2] = {(cuuint64_t)cols, (cuuint64_t)rows};
  cuuint64_t gs[1] = {(cuuint64_t)cols * 2};
  cuuint32_t box[2] = {(cuuint32_t)boxcols, (cuuint32_t)boxrows}, es[2] = {1, 1};
  enc(m, CU_TENSOR_MAP_DATA_TYPE_BFLOAT16, 2, const_cast<void*>(p), gd, gs, box, es, CU_TENSOR_MAP_INTERLEAVE_NONE,
      boxcols == 64 ? CU_TENSOR_MAP_SWIZZLE_128B : CU_TENSOR_MAP_SWIZZLE_NONE, CU_TENSOR_MAP_L2_PROMOTION_L2_128B, CU_TENSOR_MAP_FLOAT_OOB_FILL_NONE);
}
static void make_map3(EncodeFn enc, CUtensorMap* m, const void* p, int rows, int gcols) {
  cuuint64_t gd[3] = {(cuuint64_t)gcols, 8, (cuuint64_t)rows};
  cuuint64_t gs[2] = {(cuuint64_t)gcols * 2, (cuuint64_t)gcols * 16};
  cuuint32_t box[3] = {64, 1, 64}, es[3] = {1, 1, 1};
  enc(m, CU_TENSOR_MAP_DATA_TYPE_BFLOAT16, 3, const_cast<void*>(p), gd, gs, box, es, CU_TENSOR_MAP_INTERLEAVE_NONE,
      CU_TENSOR_MAP_SWIZZLE_128B, CU_TENSOR_MAP_L2_PROMOTION_L2_128B, CU_TENSOR_MAP_FLOAT_OOB_FILL_NONE);
}
template <class... P, class... A>
static void launch(void (*k)(P...), int grid, int block, int smem, bool pdl, bool pair, A... args) {
  cudaLaunchConfig_t cfg = {};
  cfg.gridDim = dim3(grid); cfg.blockDim = dim3(block); cfg.dynamicSmemBytes = smem; cfg.stream = cudaStreamPerThread;
  cudaLaunchAttribute at[2];
  int n = 0;
  if (pdl) { at[n].id = cudaLaunchAttributeProgrammaticStreamSerialization; at[n].val.programmaticStreamSerializationAllowed = 1; n++; }
  if (pair) { at[n].id = cudaLaunchAttributeClusterDimension; at[n].val.clusterDim.x = 2; at[n].val.clusterDim.y = 1; at[n].val.clusterDim.z = 1; n++; }
  cfg.attrs = at; cfg.numAttrs = n;
  cudaLaunchKernelEx(&cfg, k, args...);
}

extern "C" void kernel_launch(void* const* d_in, const int* in_sizes, int n_in, void* d_out, int out_size) {
  static EncodeFn enc = nullptr;
  static void *p_o = nullptr, *p_x1 = nullptr;
  if (!enc) {
    void* fn = nullptr;
    cudaDriverEntryPointQueryResult q;
    cudaGetDriverEntryPoint("cuTensorMapEncodeTiled", &fn, cudaEnableDefault, &q);
    enc = (EncodeFn)fn;
    cudaGetSymbolAddress(&p_o, g_o);
    cudaGetSymbolAddress(&p_x1, g_x1);
    cudaFuncSetAttribute(qkv_kernel, cudaFuncAttributeMaxDynamicSharedMemorySize, SMEM_GEMM);
    cudaFuncSetAttribute(attn_kernel, cudaFuncAttributeMaxDynamicSharedMemorySize, SMEM_ATT);
    cudaFuncSetAttribute(ffn_kernel, cudaFuncAttributeMaxDynamicSharedMemorySize, SMEM_GEMM);
  }
  const bf16 *x = (const bf16*)d_in[0], *wqkv = (const bf16*)d_in[1], *wo = (const bf16*)d_in[2], *wg = (const bf16*)d_in[4],
             *wu = (const bf16*)d_in[5], *wd = (const bf16*)d_in[6], *c = (const bf16*)d_in[7], *wmod = (const bf16*)d_in[8];
  CUtensorMap m_x, m_wqkv, m_o, m_wo, m_x1, m_g, m_u, m_d, m_out;
  make_map(enc, &m_x, x, S_, D_, 128);
  make_map3(enc, &m_wqkv, wqkv, D_, 216);
  make_map(enc, &m_o, p_o, S_, D_, 64);
  make_map3(enc, &m_wo, wo, D_, 72);
  make_map(enc, &m_x1, p_x1, S_, D_, 64);
  make_map(enc, &m_g, wg, D_, F_, 64);
  make_map(enc, &m_u, wu, D_, F_, 64);
  make_map(enc, &m_d, wd, F_, D_, 64);
  make_map(enc, &m_out, d_out, S_, D_, 16);
  launch(qkv_kernel, 128, 384, SMEM_GEMM, false, true, m_x, m_wqkv, c, wmod);
  launch(attn_kernel, 132, 512, SMEM_ATT, true, false, c, wmod, wo, wg, wu, wd);
  launch(ffn_kernel, 128, 384, SMEM_GEMM, true, true, m_o, m_wo, m_x1, m_g, m_u, m_d, m_out, x, (bf16*)d_out);
}
```
